```python
import torch

def _softmax(x, axis=-1):
    return torch.softmax(x, dim=axis)

def _gelu(x):
    return torch.nn.functional.gelu(x, approximate='tanh')

def _silu(x):
    return torch.nn.functional.silu(x)

def _sigmoid(x):
    return torch.sigmoid(x)

def _layernorm(x, axis=-1, eps=1e-05):
    m = x.mean(dim=axis, keepdim=True)
    v = x.var(dim=axis, keepdim=True, unbiased=False)
    return (x - m) / torch.sqrt(v + eps)

def _scatter_add(tgt, idx, src, axis=0):
    return tgt.clone().index_add_(axis, idx, src)

def _segment_sum(src, seg, n):
    out = torch.zeros((n,) + src.shape[1:], dtype=src.dtype)
    return out.index_add_(0, seg, src)

def _pad(x, pw):
    flat = tuple((v for pair in reversed(pw) for v in pair))
    return torch.nn.functional.pad(x, flat)
kernel_name = 'standalone__factorization_afm__recsys'

def setup_inputs():

    _w = lambda a: (lambda t: t.to(torch.bfloat16) if t.is_floating_point() else t)(torch.as_tensor(a))
    B, F, D, V = (1024, 100, 32, min(1000, 100000))
    A = D
    ii, jj = tuple(torch.triu_indices(F, F, 1).unbind(0))
    return {'idx': _w((lambda lo, hi, *s: torch.randint(lo, hi, s))(0, V, B, F).to(torch.int64)), 'table': _w((lambda *s: torch.randn(*s, dtype=torch.bfloat16) * 0.8)(V, D)), 'ii': _w(ii.to(torch.int64)), 'jj': _w(jj.to(torch.int64)), 'W': _w((lambda *s: torch.randn(*s, dtype=torch.bfloat16) * 0.8)(D, A) * (1.0 / D ** 0.5)), 'b': _w((lambda *s: torch.randn(*s, dtype=torch.bfloat16) * 0.8)(A)), 'h': _w((lambda *s: torch.randn(*s, dtype=torch.bfloat16) * 0.8)(A)), 'p': _w((lambda *s: torch.randn(*s, dtype=torch.bfloat16) * 0.8)(D))}

def reference(idx, table, ii, jj, W, b, h, p):
    emb = table[idx]
    ei = emb[:, ii, :].clone()
    ej = emb[:, jj, :].clone()
    pair = ei * ej
    hid = pair @ W + b
    hid = 0.5 * (hid + torch.abs(hid))
    e = hid @ h
    alpha = _softmax(e, axis=-1)
    pooled = torch.einsum('bp,bpd->bd', alpha, pair)
    return pooled @ p
```

```cpp
#include <cuda_runtime.h>
#include <cuda_bf16.h>
#include <stdint.h>

#define STAMP(i)
#define STAMPA(i)
#define FSC(i)

namespace {

constexpr int kF = 100, kD = 32, kV = 1000, kP = 4950;
constexpr int kV16 = 63;
constexpr int kTiles = 66;
constexpr int kGrid = 132;
constexpr int kThreads = 512;
constexpr int kQuart = 61440;

constexpr int OFF_C = 0;
constexpr int OFF_B2 = OFF_C + 2 * kQuart;
constexpr int OFF_G = OFF_B2 + 36864;
constexpr int OFF_CB = OFF_G + 50688;
constexpr int OFF_CST = OFF_CB + 8064;
constexpr int OFF_RED = OFF_CST + 256;
constexpr int OFF_DUP = OFF_RED + 320;
constexpr int OFF_BAR = OFF_DUP + 4096;
constexpr int OFF_MISC = OFF_BAR + 64;
constexpr int SMEM_BYTES = OFF_MISC + 64;
constexpr int ST_TU = OFF_C;
constexpr int ST_TV = ST_TU + 15360;
constexpr int ST_W = ST_TV + 1920;

__device__ uint4 g_C[16 * kV16 * 64];
__device__ uint4 g_part[128 * kTiles * 4];
__device__ uint2 g_diag[1024];
__device__ unsigned g_cnt[5 * 32];

__device__ __forceinline__ uint32_t smem_u32(const void* p) {
    return (uint32_t)__cvta_generic_to_shared(p);
}
__device__ __forceinline__ uint64_t make_desc(uint32_t addr, uint32_t lbo, uint32_t sbo) {
    return (uint64_t)((addr & 0x3FFFF) >> 4) | ((uint64_t)(lbo >> 4) << 16) | ((uint64_t)(sbo >> 4) << 32);
}
__device__ __forceinline__ void wg_fence() { asm volatile("wgmma.fence.sync.aligned;" ::: "memory"); }
__device__ __forceinline__ void wg_commit() { asm volatile("wgmma.commit_group.sync.aligned;" ::: "memory"); }
template <int N>
__device__ __forceinline__ void wg_wait() { asm volatile("wgmma.wait_group.sync.aligned %0;" ::"n"(N) : "memory"); }

__device__ __forceinline__ void mma_n24(float (&d)[12], uint32_t a0, uint32_t a1, uint32_t a2, uint32_t a3,
                                        uint64_t desc, int scale_d) {
    asm volatile(
        "{\n.reg .pred p;\nsetp.ne.b32 p, %17, 0;\n"
        "wgmma.mma_async.sync.aligned.m64n24k16.f32.bf16.bf16 "
        "{%0,%1,%2,%3,%4,%5,%6,%7,%8,%9,%10,%11},"
        "{%12,%13,%14,%15}, %16, p, 1, 1, 0;\n}\n"
        : "+f"(d[0]), "+f"(d[1]), "+f"(d[2]), "+f"(d[3]), "+f"(d[4]), "+f"(d[5]), "+f"(d[6]), "+f"(d[7]),
          "+f"(d[8]), "+f"(d[9]), "+f"(d[10]), "+f"(d[11])
        : "r"(a0), "r"(a1), "r"(a2), "r"(a3), "l"(desc), "r"(scale_d));
}

__device__ __forceinline__ void mma_h96(uint32_t (&d)[24], uint32_t a0, uint32_t a1, uint32_t a2, uint32_t a3,
                                        uint64_t desc, int scale_d) {
    asm volatile(
        "{\n.reg .pred p;\nsetp.ne.b32 p, %29, 0;\n"
        "wgmma.mma_async.sync.aligned.m64n96k16.f16.f16.f16 "
        "{%0,%1,%2,%3,%4,%5,%6,%7,%8,%9,%10,%11,%12,%13,%14,%15,%16,%17,%18,%19,%20,%21,%22,%23},"
        "{%24,%25,%26,%27}, %28, p, 1, 1, 0;\n}\n"
        : "+r"(d[0]), "+r"(d[1]), "+r"(d[2]), "+r"(d[3]), "+r"(d[4]), "+r"(d[5]), "+r"(d[6]), "+r"(d[7]),
          "+r"(d[8]), "+r"(d[9]), "+r"(d[10]), "+r"(d[11]), "+r"(d[12]), "+r"(d[13]), "+r"(d[14]), "+r"(d[15]),
          "+r"(d[16]), "+r"(d[17]), "+r"(d[18]), "+r"(d[19]), "+r"(d[20]), "+r"(d[21]), "+r"(d[22]), "+r"(d[23])
        : "r"(a0), "r"(a1), "r"(a2), "r"(a3), "l"(desc), "r"(scale_d));
}

__device__ __forceinline__ void mma_n96(float (&d)[48], uint32_t a0, uint32_t a1, uint32_t a2, uint32_t a3,
                                        uint64_t desc, int scale_d) {
    asm volatile(
        "{\n.reg .pred p;\nsetp.ne.b32 p, %53, 0;\n"
        "wgmma.mma_async.sync.aligned.m64n96k16.f32.bf16.bf16 "
        "{%0,%1,%2,%3,%4,%5,%6,%7,%8,%9,%10,%11,%12,%13,%14,%15,%16,%17,%18,%19,%20,%21,%22,%23,"
        "%24,%25,%26,%27,%28,%29,%30,%31,%32,%33,%34,%35,%36,%37,%38,%39,%40,%41,%42,%43,%44,%45,%46,%47},"
        "{%48,%49,%50,%51}, %52, p, 1, 1, 0;\n}\n"
        : "+f"(d[0]), "+f"(d[1]), "+f"(d[2]), "+f"(d[3]), "+f"(d[4]), "+f"(d[5]), "+f"(d[6]), "+f"(d[7]),
          "+f"(d[8]), "+f"(d[9]), "+f"(d[10]), "+f"(d[11]), "+f"(d[12]), "+f"(d[13]), "+f"(d[14]), "+f"(d[15]),
          "+f"(d[16]), "+f"(d[17]), "+f"(d[18]), "+f"(d[19]), "+f"(d[20]), "+f"(d[21]), "+f"(d[22]), "+f"(d[23]),
          "+f"(d[24]), "+f"(d[25]), "+f"(d[26]), "+f"(d[27]), "+f"(d[28]), "+f"(d[29]), "+f"(d[30]), "+f"(d[31]),
          "+f"(d[32]), "+f"(d[33]), "+f"(d[34]), "+f"(d[35]), "+f"(d[36]), "+f"(d[37]), "+f"(d[38]), "+f"(d[39]),
          "+f"(d[40]), "+f"(d[41]), "+f"(d[42]), "+f"(d[43]), "+f"(d[44]), "+f"(d[45]), "+f"(d[46]), "+f"(d[47])
        : "r"(a0), "r"(a1), "r"(a2), "r"(a3), "l"(desc), "r"(scale_d));
}

__device__ __forceinline__ uint32_t bmul2(uint32_t a, uint32_t b) {
    uint32_t r;
    asm("mul.rn.bf16x2 %0, %1, %2;" : "=r"(r) : "r"(a), "r"(b));
    return r;
}
__device__ __forceinline__ uint32_t pack_bf16(float lo, float hi) {
    uint32_t r;
    asm("cvt.rn.bf16x2.f32 %0, %1, %2;" : "=r"(r) : "f"(hi), "f"(lo));
    return r;
}
__device__ __forceinline__ float bf_lo(uint32_t x) { return __uint_as_float(x << 16); }
__device__ __forceinline__ float bf_hi(uint32_t x) { return __uint_as_float(x & 0xffff0000u); }
__device__ __forceinline__ uint32_t pack_f16(float lo, float hi) {
    uint32_t r;
    asm("cvt.rn.f16x2.f32 %0, %1, %2;" : "=r"(r) : "f"(hi), "f"(lo));
    return r;
}
__device__ __forceinline__ uint32_t bf2h(uint32_t x) { return pack_f16(bf_lo(x), bf_hi(x)); }
__device__ __forceinline__ uint32_t hmul2(uint32_t a, uint32_t b) {
    uint32_t r;
    asm("mul.rn.f16x2 %0, %1, %2;" : "=r"(r) : "r"(a), "r"(b));
    return r;
}
__device__ __forceinline__ uint32_t hfma2(uint32_t a, uint32_t b, uint32_t c) {
    uint32_t r;
    asm("fma.rn.f16x2 %0, %1, %2, %3;" : "=r"(r) : "r"(a), "r"(b), "r"(c));
    return r;
}
__device__ __forceinline__ uint32_t hadd2_relu(uint32_t a, uint32_t c) {
    uint32_t r;
    asm("fma.rn.relu.f16x2 %0, %1, %2, %3;" : "=r"(r) : "r"(a), "r"(0x3C003C00u), "r"(c));
    return r;
}
__device__ __forceinline__ float h_lo(uint32_t x) {
    float r;
    asm("{.reg .f16 l, h; mov.b32 {l, h}, %1; cvt.f32.f16 %0, l;}" : "=f"(r) : "r"(x));
    return r;
}
__device__ __forceinline__ float h_hi(uint32_t x) {
    float r;
    asm("{.reg .f16 l, h; mov.b32 {l, h}, %1; cvt.f32.f16 %0, h;}" : "=f"(r) : "r"(x));
    return r;
}
template <int LOG2>
__device__ __forceinline__ bool bf_exceeds(uint32_t a, uint32_t b, uint32_t c, uint32_t d) {
    const uint32_t m = 0x7fff7fffu;
    const uint32_t mx = __vmaxu2(__vmaxu2(a & m, b & m), __vmaxu2(c & m, d & m));
    return __vcmpgtu2(mx, ((127u + LOG2) << 7) * 0x10001u) != 0;
}
__device__ __forceinline__ float ex2(float x) {
    float r;
    asm("ex2.approx.ftz.f32 %0, %1;" : "=f"(r) : "f"(x));
    return r;
}
__device__ __forceinline__ float maxnan_abs(float m, float x) {
    float r;
    asm("max.NaN.f32 %0, %1, %2;" : "=f"(r) : "f"(m), "f"(fabsf(x)));
    return r;
}
__device__ __forceinline__ uint4 lds128(uint32_t a) {
    uint4 v;
    asm volatile("ld.shared.v4.u32 {%0,%1,%2,%3}, [%4];" : "=r"(v.x), "=r"(v.y), "=r"(v.z), "=r"(v.w) : "r"(a));
    return v;
}
__device__ __forceinline__ uint2 lds64(uint32_t a) {
    uint2 v;
    asm volatile("ld.shared.v2.u32 {%0,%1}, [%2];" : "=r"(v.x), "=r"(v.y) : "r"(a));
    return v;
}
__device__ __forceinline__ uint32_t lds32(uint32_t a) {
    uint32_t v;
    asm volatile("ld.shared.u32 %0, [%1];" : "=r"(v) : "r"(a) : "memory");
    return v;
}
__device__ __forceinline__ uint32_t lds32_nv(uint32_t a) {
    uint32_t v;
    asm("ld.shared.u32 %0, [%1];" : "=r"(v) : "r"(a));
    return v;
}
__device__ __forceinline__ uint32_t opaque(uint32_t a) {
    asm volatile("" : "+r"(a) :: "memory");
    return a;
}
__device__ __forceinline__ void sts128(uint32_t a, uint4 v) {
    asm volatile("st.shared.v4.u32 [%0], {%1,%2,%3,%4};" ::"r"(a), "r"(v.x), "r"(v.y), "r"(v.z), "r"(v.w) : "memory");
}
__device__ __forceinline__ void sts64(uint32_t a, uint32_t x, uint32_t y) {
    asm volatile("st.shared.v2.u32 [%0], {%1,%2};" ::"r"(a), "r"(x), "r"(y) : "memory");
}
__device__ __forceinline__ void sts16(uint32_t a, uint32_t x) {
    asm volatile("st.shared.u16 [%0], %1;" ::"r"(a), "h"((unsigned short)x) : "memory");
}
__device__ __forceinline__ void sts32(uint32_t a, uint32_t x) {
    asm volatile("st.shared.u32 [%0], %1;" ::"r"(a), "r"(x) : "memory");
}
__device__ __forceinline__ void mbar_wait(uint32_t bar, uint32_t parity) {
    uint32_t done = 0;
    for (int it = 0; it < (1 << 20) && !done; ++it) {
        asm volatile(
            "{\n.reg .pred p;\nmbarrier.try_wait.parity.shared::cta.b64 p, [%1], %2;\nselp.u32 %0, 1, 0, p;\n}\n"
            : "=r"(done) : "r"(bar), "r"(parity) : "memory");
    }
}
__device__ __forceinline__ void mbar_wait_cluster(uint32_t bar, uint32_t parity) {
    uint32_t done = 0;
    for (int it = 0; it < (1 << 20) && !done; ++it) {
        asm volatile(
            "{\n.reg .pred p;\nmbarrier.try_wait.parity.acquire.cluster.shared::cta.b64 p, [%1], %2;\nselp.u32 %0, 1, 0, p;\n}\n"
            : "=r"(done) : "r"(bar), "r"(parity) : "memory");
    }
}
__device__ __forceinline__ void cp16(uint32_t dst, const void* src, bool valid) {
    asm volatile("cp.async.cg.shared.global [%0], [%1], 16, %2;" ::"r"(dst), "l"(src), "r"(valid ? 16 : 0) : "memory");
}
#define BAR_SYNC(id, n) asm volatile("bar.sync " #id ", " #n ";" ::: "memory")
#define BAR_ARRIVE(id, n) asm volatile("bar.arrive " #id ", " #n ";" ::: "memory")
template <int SEL>
__device__ __forceinline__ uint32_t cnt2bf(uint32_t w) {
    uint32_t r;
    asm volatile("{\n.reg .b32 t;\nprmt.b32 t, %1, 0x43434343, %2;\nadd.rn.bf16x2 %0, t, %3;\n}\n"
                 : "=r"(r) : "r"(w), "n"(SEL), "r"(0xC300C300u));
    return r;
}
template <int SEL>
__device__ __forceinline__ float cnt2f(uint32_t w) {
    float r;
    asm volatile("{\n.reg .b32 t;\nprmt.b32 t, %1, 0x4B000000, %2;\nadd.rn.f32 %0, t, 0fCB000000;\n}\n"
                 : "=f"(r) : "r"(w), "n"(SEL));
    return r;
}

__device__ __noinline__ void fallback_rows(const int* __restrict__ idx, const __nv_bfloat16* __restrict__ table,
                                           const int* __restrict__ ii, const int* __restrict__ jj,
                                           const __nv_bfloat16* __restrict__ W, const __nv_bfloat16* __restrict__ bv,
                                           const __nv_bfloat16* __restrict__ hv, const __nv_bfloat16* __restrict__ pv,
                                           __nv_bfloat16* __restrict__ out, unsigned char* smem, int b0, int tid) {
    float* sW = reinterpret_cast<float*>(smem);
    float* sb = sW + 1024;
    float* sh = sb + 32;
    float* sp = sh + 32;
    float* sE = sp + 32;
    float* sR = sE + kF * 33;
    for (int i = tid; i < 1024; i += 384) sW[i] = __bfloat162float(W[i]);
    if (tid < 32) {
        sb[tid] = __bfloat162float(bv[tid]);
        sh[tid] = __bfloat162float(hv[tid]);
        sp[tid] = __bfloat162float(pv[tid]);
    }
    for (int r = 0; r < 8; ++r) {
        const int b = b0 + r;
        BAR_SYNC(6, 384);
        for (int i = tid; i < kF * kD; i += 384) {
            int f = i >> 5, d = i & 31;
            int v = idx[b * kF + f];
            if (v < 0) v += kV;
            v = min(max(v, 0), kV - 1);
            sE[f * 33 + d] = __bfloat162float(table[v * kD + d]);
        }
        BAR_SYNC(6, 384);
        float m = -INFINITY, z = 0.f, n = 0.f;
        for (int k = tid; k < kP; k += 384) {
            int i = ii[k], j = jj[k];
            if (i < 0) i += kF;
            if (j < 0) j += kF;
            i = min(max(i, 0), kF - 1);
            j = min(max(j, 0), kF - 1);
            float hid[32];
#pragma unroll
            for (int a = 0; a < 32; ++a) hid[a] = sb[a];
            float s = 0.f;
            for (int d = 0; d < 32; ++d) {
                float pr = __bfloat162float(__float2bfloat16(sE[i * 33 + d] * sE[j * 33 + d]));
                s = fmaf(pr, sp[d], s);
#pragma unroll
                for (int a = 0; a < 32; a += 4) {
                    float4 w = *reinterpret_cast<const float4*>(sW + d * 32 + a);
                    hid[a] = fmaf(pr, w.x, hid[a]);
                    hid[a + 1] = fmaf(pr, w.y, hid[a + 1]);
                    hid[a + 2] = fmaf(pr, w.z, hid[a + 2]);
                    hid[a + 3] = fmaf(pr, w.w, hid[a + 3]);
                }
            }
            float e = 0.f;
#pragma unroll
            for (int a = 0; a < 32; ++a) e = fmaf(0.5f * (hid[a] + fabsf(hid[a])), sh[a], e);
            float mn = fmaxf(m, e);
            float c = __expf(m - mn), w = __expf(e - mn);
            if (m == -INFINITY) c = 0.f;
            z = z * c + w;
            n = n * c + w * s;
            m = mn;
        }
#pragma unroll
        for (int o = 16; o > 0; o >>= 1) {
            float m2 = __shfl_xor_sync(0xffffffffu, m, o);
            float z2 = __shfl_xor_sync(0xffffffffu, z, o);
            float n2 = __shfl_xor_sync(0xffffffffu, n, o);
            float mn = fmaxf(m, m2);
            float c1 = (m == -INFINITY) ? 0.f : __expf(m - mn);
            float c2 = (m2 == -INFINITY) ? 0.f : __expf(m2 - mn);
            z = z * c1 + z2 * c2;
            n = n * c1 + n2 * c2;
            m = mn;
        }
        if ((tid & 31) == 0) {
            sR[(tid >> 5) * 3 + 0] = m;
            sR[(tid >> 5) * 3 + 1] = z;
            sR[(tid >> 5) * 3 + 2] = n;
        }
        BAR_SYNC(6, 384);
        if (tid == 0) {
            float mm = -INFINITY;
            for (int w = 0; w < 12; ++w) mm = fmaxf(mm, sR[w * 3]);
            float zz = 0.f, nn = 0.f;
            for (int w = 0; w < 12; ++w) {
                float c = (sR[w * 3] == -INFINITY) ? 0.f : __expf(sR[w * 3] - mm);
                zz += sR[w * 3 + 1] * c;
                nn += sR[w * 3 + 2] * c;
            }
            out[b] = __float2bfloat16(nn / zz);
        }
    }
}

__global__ void __launch_bounds__(384, 1)
afm_direct_kernel(const int* __restrict__ idx, const __nv_bfloat16* __restrict__ table,
                  const int* __restrict__ ii, const int* __restrict__ jj,
                  const __nv_bfloat16* __restrict__ W, const __nv_bfloat16* __restrict__ bv,
                  const __nv_bfloat16* __restrict__ hv, const __nv_bfloat16* __restrict__ pv,
                  __nv_bfloat16* __restrict__ out) {
    __shared__ __align__(16) unsigned char sm[18432];
    fallback_rows(idx, table, ii, jj, W, bv, hv, pv, out, sm, blockIdx.x * 8, threadIdx.x);
}

struct TileMap { unsigned char v[kTiles + 2]; };

__global__ void __cluster_dims__(2, 1, 1) __launch_bounds__(kThreads, 1)
afm_kernel(const int* __restrict__ idx, const __nv_bfloat16* __restrict__ table,
           const int* __restrict__ ii, const int* __restrict__ jj,
           const __nv_bfloat16* __restrict__ W, const __nv_bfloat16* __restrict__ bv,
           const __nv_bfloat16* __restrict__ hv, const __nv_bfloat16* __restrict__ pv,
           __nv_bfloat16* __restrict__ out, uint4* __restrict__ gC, uint4* __restrict__ gPart,
           uint2* __restrict__ gDiag, unsigned* __restrict__ gCnt, const __grid_constant__ TileMap tmap) {
    extern __shared__ __align__(1024) unsigned char smem[];
    const uint32_t sbase = smem_u32(smem);
    const int T = threadIdx.x;
    const int lane = T & 31;
    const int cta = blockIdx.x;
    const int tile = cta >> 1, rank = cta & 1;
    const bool builder = cta < 128;
    STAMP(0);

    const int tcode = tmap.v[tile];
    const int tI = tcode >> 5, tj = tcode & 31;
    const int vb0 = tj * 48 + rank * 24;
    const float kLog2e = 1.44269504088896340736f;
    const uint32_t sMisc = sbase + OFF_MISC;

    if (T < 128) {
        asm volatile("setmaxnreg.dec.sync.aligned.u32 56;");
        const int t = T;
        unsigned* myCnt = gCnt + (cta >> 5) * 32;
        const int j = t - 32;
        uint4 y4 = make_uint4(0, 0, 0, 0), y5 = y4, z4 = y4, p4 = y4;
        if (t >= 32) {
            y4 = __ldg(reinterpret_cast<const uint4*>(W) + j);
            if (j < 32) y5 = __ldg(reinterpret_cast<const uint4*>(W) + 96 + j);
            if (vb0 + (j >> 2) < kV) z4 = __ldg(reinterpret_cast<const uint4*>(table + (vb0 + (j >> 2)) * kD) + (j & 3));
            p4 = __ldg(reinterpret_cast<const uint4*>(pv) + (j & 3));
        }
        uint32_t x0 = 0, x1 = 0, x2 = 0, x3 = 0;
        if (t >= 64) {
            const int kc = min(cta * 38 + (t - 64), kP - 1), kp = max(kc - 1, 0);
            x0 = __ldg(ii + kc); x1 = __ldg(jj + kc); x2 = __ldg(ii + kp); x3 = __ldg(jj + kp);
        } else if (t >= 32) {
            x0 = __ldg(reinterpret_cast<const unsigned short*>(bv) + lane);
            x1 = __ldg(reinterpret_cast<const unsigned short*>(hv) + lane);
        }
        uint32_t xe;
        asm volatile("ld.relaxed.gpu.global.u32 %0, [%1];" : "=r"(xe) : "l"(myCnt) : "memory");
        if (t == 0) {
#pragma unroll
            for (int i = 0; i < 3; ++i)
                asm volatile("mbarrier.init.shared::cta.b64 [%0], 1;" ::"r"(sbase + OFF_BAR + i * 8) : "memory");
            const uint32_t qbytes = min(12, kV16 - tI * 12) * 4096 + 12288;
            asm volatile("mbarrier.arrive.expect_tx.shared::cta.b64 _, [%0], %1;" ::"r"(sbase + OFF_BAR), "r"(qbytes) : "memory");
            asm volatile("mbarrier.arrive.expect_tx.shared::cta.b64 _, [%0], %1;" ::"r"(sbase + OFF_BAR + 8), "r"(qbytes) : "memory");
            asm volatile("mbarrier.arrive.expect_tx.shared::cta.b64 _, [%0], %1;" ::"r"(sbase + OFF_BAR + 16), "r"(18432) : "memory");
            asm volatile("fence.mbarrier_init.release.cluster;" ::: "memory");
        }
        if (t == 32) sts32(sMisc + 4, 0);
        __syncwarp();
        asm volatile("barrier.cluster.arrive.relaxed.aligned;" ::: "memory");
        BAR_SYNC(7, 128);
        if (t < 32) {
            BAR_SYNC(1, 416);
            STAMPA(14);
            if (t == 0) asm volatile("red.release.gpu.global.add.u32 [%0], 1;" ::"l"(myCnt) : "memory");
            STAMPA(8);
        } else {
            auto put_wt = [&](const uint4& y, int c) {
                const uint32_t wt = sbase + ST_W + (c & 3) * 640 + (c >> 2) * 2;
                const uint32_t w0 = bf2h(y.x), w1 = bf2h(y.y), w2 = bf2h(y.z), w3 = bf2h(y.w);
                sts16(wt, w0); sts16(wt + 80, w0 >> 16); sts16(wt + 160, w1); sts16(wt + 240, w1 >> 16);
                sts16(wt + 320, w2); sts16(wt + 400, w2 >> 16); sts16(wt + 480, w3); sts16(wt + 560, w3 >> 16);
            };
            sts128(sbase + ST_TV + (j >> 2) * 80 + (j & 3) * 16, make_uint4(bf2h(z4.x), bf2h(z4.y), bf2h(z4.z), bf2h(z4.w)));
            put_wt(y4, j);
            if (j < 32) put_wt(y5, 96 + j);
            BAR_ARRIVE(2, 480);
            {
                const int kb = j & 3, vl = j >> 2;
                sts128(sbase + OFF_G + 49152 + (vl >> 3) * 512 + kb * 128 + (vl & 7) * 16,
                       make_uint4(bmul2(z4.x, p4.x), bmul2(z4.y, p4.y), bmul2(z4.z, p4.z), bmul2(z4.w, p4.w)));
            }
            bool bad = bf_exceeds<3>(y4.x, y4.y, y4.z, y4.w) || bf_exceeds<3>(y5.x, y5.y, y5.z, y5.w) ||
                       bf_exceeds<4>(z4.x, z4.y, z4.z, z4.w);
            if (t < 64) {
                const float bb = __uint_as_float(x0 << 16), hh = __uint_as_float(x1 << 16) * kLog2e;
                sts32(sbase + OFF_CST + (lane >> 2) * 32 + (lane & 3) * 4, pack_f16(bb, bb));
                sts32(sbase + OFF_CST + (lane >> 2) * 32 + 16 + (lane & 3) * 4, pack_f16(hh, hh));
                bad |= !(fabsf(hh) <= 8.f);
                float mm = hh * fmaxf(bb, 0.f);
#pragma unroll
                for (int o = 16; o > 0; o >>= 1) mm += __shfl_xor_sync(0xffffffffu, mm, o);
                if (lane == 0) sts32(sMisc + 12, __float_as_uint(-mm));
            } else {
                if (t == 64) sts32(sMisc, builder ? (xe >> 5) : (xe >> 2));
                const int kk = cta * 38 + (t - 64);
                if (t < 64 + 38 && kk < kP) {
                    const int ci = x0, cj = x1, pi = x2, pj = x3;
                    int ei, ej;
                    if (kk == 0) { ei = 0; ej = 1; }
                    else if (pj + 1 < kF) { ei = pi; ej = pj + 1; }
                    else { ei = pi + 1; ej = pi + 2; }
                    bad |= (ci != ei || cj != ej);
                }
            }
            if (bad) sts32(sMisc + 4, 1);
            asm volatile("fence.proxy.async.shared::cta;" ::: "memory");
            BAR_ARRIVE(14, 480);
        }
        const unsigned epoch = __shfl_sync(0xffffffffu, builder ? (xe >> 5) : (xe >> 2), 0);
        const uint32_t tag = (epoch + 1) & 3;
        if (t >= 64) {
            BAR_SYNC(13, 512);
        } else {
            const int w = t >> 5;
            const unsigned target = (epoch + 1) << 5;
            const unsigned* cp = gCnt + (rank * 2 + w) * 32;
            const uint32_t abytes = min(12, kV16 - tI * 12) * 4096;
            const unsigned char* gb = reinterpret_cast<const unsigned char*>(gC) + (rank * 2 + w) * (kV16 * 4096);
            const uint32_t bar = sbase + OFF_BAR + w * 8;
            const uint32_t dst = sbase + OFF_C + w * kQuart;
            BAR_SYNC(13, 512);
            if (lane == 0) {
                unsigned c;
                for (int it = 0; it < (1 << 20); ++it) {
                    asm volatile("ld.acquire.gpu.global.u32 %0, [%1];" : "=r"(c) : "l"(cp) : "memory");
                    if ((int)(c - target) >= 0) break;
                }
                asm volatile("fence.proxy.async.global;" ::: "memory");
                asm volatile("cp.async.bulk.shared::cluster.global.mbarrier::complete_tx::bytes [%0], [%1], %2, [%3];"
                             ::"r"(dst), "l"(gb + tI * 49152), "r"(abytes), "r"(bar) : "memory");
                asm volatile("cp.async.bulk.shared::cluster.global.mbarrier::complete_tx::bytes [%0], [%1], %2, [%3];"
                             ::"r"(dst + 49152), "l"(gb + tj * 12288), "r"(12288), "r"(bar) : "memory");
            }
            __syncwarp();
            STAMPA(9);
        }
        {
            uint32_t dv[8] = {0, 0, 0, 0, 0, 0, 0, 0};
            if (builder) {
                const int row = t >> 4;
                const int* ip = idx + (cta * 8 + row) * kF + (t & 15);
                unsigned vals[7];
#pragma unroll
                for (int i = 0; i < 7; ++i) vals[i] = __ldg(ip + min(16 * i, 99 - (t & 15)));
                const uint32_t rb = opaque(sbase + OFF_CB + (row >> 1) * 32 + (row & 1) * 4);
#pragma unroll
                for (int i = 0; i < 7; ++i) {
                    const unsigned v = min(vals[i], 1007u);
                    uint32_t c = (lds32_nv(rb + (v >> 4) * 128 + ((v << 2) & 24)) >>
                                  (((v << 1) & 16) + ((v & 1) << 3))) & 0xff;
                    if (i == 6 && (t & 15) >= 4) c = 1;
                    dv[i] = v | (c << 16);
                }
            }
            sts128(sbase + OFF_DUP + t * 32, make_uint4(dv[0], dv[1], dv[2], dv[3]));
            sts128(sbase + OFF_DUP + t * 32 + 16, make_uint4(dv[4], dv[5], dv[6], dv[7]));
            BAR_ARRIVE(15, 256);
        }
        BAR_SYNC(3, 512);
        STAMPA(10);
        if (builder) {
            const uint4* src = gPart + (size_t)cta * (kTiles * 4) + lane * 4 + (t >> 5);
            const uint32_t tg4 = tag;
            auto ld = [&](uint4& v, const uint4* ptr, bool on) {
                asm volatile("{\n.reg .pred p;\nsetp.ne.u32 p, %5, 0;\n"
                             "@p ld.relaxed.gpu.global.v4.u32 {%0,%1,%2,%3}, [%4];\n}\n"
                             : "+r"(v.x), "+r"(v.y), "+r"(v.z), "+r"(v.w) : "l"(ptr), "r"((uint32_t)on) : "memory");
            };
            auto stale = [&](const uint4& v) { return (((v.x ^ tg4) | (v.y ^ tg4) | (v.z ^ tg4) | (v.w ^ tg4)) & 3u) != 0; };
            const uint4 none = make_uint4(tg4, tg4, tg4, tg4), inv = make_uint4(~tg4, 0, 0, 0);
            uint4 a0 = inv, a1 = inv, a2 = lane < kTiles - 64 ? inv : none;
            for (int spin = 0; spin < (1 << 20); ++spin) {
                const bool p0 = stale(a0), p1 = stale(a1), p2 = stale(a2);
                if (!__any_sync(0xffffffffu, p0 || p1 || p2)) break;
                uint4 b0 = a0, b1 = a1, b2 = a2;
                ld(a0, src, p0); ld(a1, src + 128, p1); ld(a2, src + 256, p2);
                __nanosleep(150);
                ld(b0, src, p0); ld(b1, src + 128, p1); ld(b2, src + 256, p2);
                if (!__any_sync(0xffffffffu, stale(a0) || stale(a1) || stale(a2))) break;
                if (stale(a0)) a0 = b0;
                if (stale(a1)) a1 = b1;
                if (stale(a2)) a2 = b2;
            }
            float s0 = __uint_as_float(a0.x & ~3u) + __uint_as_float(a1.x & ~3u) + __uint_as_float(a2.x & ~3u);
            float s1 = __uint_as_float(a0.y & ~3u) + __uint_as_float(a1.y & ~3u) + __uint_as_float(a2.y & ~3u);
            float s2 = __uint_as_float(a0.z & ~3u) + __uint_as_float(a1.z & ~3u) + __uint_as_float(a2.z & ~3u);
            float s3 = __uint_as_float(a0.w & ~3u) + __uint_as_float(a1.w & ~3u) + __uint_as_float(a2.w & ~3u);
            STAMPA(6);
            const bool odd = lane & 1;
            float z = (odd ? s2 : s0) + __shfl_xor_sync(0xffffffffu, odd ? s0 : s2, 1);
            float n = (odd ? s3 : s1) + __shfl_xor_sync(0xffffffffu, odd ? s1 : s3, 1);
#pragma unroll
            for (int o = 2; o < 32; o <<= 1) {
                z += __shfl_xor_sync(0xffffffffu, z, o);
                n += __shfl_xor_sync(0xffffffffu, n, o);
            }
            BAR_SYNC(12, 256);
            if (lane < 2) {
                const int row = (t >> 5) * 2 + lane;
                const uint2 v = lds64(sbase + OFF_RED + 256 + row * 8);
                z += __uint_as_float(v.x);
                n += __uint_as_float(v.y);
                if (!(z > 0.f && z < 3.0e38f && fabsf(n) < 3.0e38f)) sts32(sMisc + 8, 1);
                out[cta * 8 + row] = __float2bfloat16(__fdividef(n, z));
            }
            STAMPA(7);
        } else {
            BAR_SYNC(12, 256);
        }
        __syncwarp();
        BAR_ARRIVE(5, 512);
    } else {
        asm volatile("setmaxnreg.inc.sync.aligned.u32 152;");
        const int tid = T - 128;
        const int warp = tid >> 5;
        const int r = lane >> 2, q = lane & 3;
        const int wg = warp >> 2, wq = warp & 3;
        const int u = tI * 192 + warp * 16 + r;
        int4 iv = make_int4(0, 0, 0, 0);
        if (tid < 200) iv = __ldg(reinterpret_cast<const int4*>(idx + (builder ? cta : 0) * 8 * kF) + tid);
        {
            const int ur = tI * 192 + warp * 16 + (lane >> 1);
            const uint32_t dst = sbase + ST_TU + (warp * 16 + (lane >> 1)) * 80 + (lane & 1) * 32;
            const __nv_bfloat16* src = table + min(ur, kV - 1) * kD + (lane & 1) * 16;
            cp16(dst, src, ur < kV);
            cp16(dst + 16, src + 8, ur < kV);
        }
        sts128(sbase + OFF_CB + tid * 16, make_uint4(0, 0, 0, 0));
        if (tid < 120) sts128(sbase + OFF_CB + (384 + tid) * 16, make_uint4(0, 0, 0, 0));
        if (tid == 383) sts32(sMisc + 8, 0);
        asm volatile("barrier.cluster.arrive.relaxed.aligned;" ::: "memory");
        BAR_SYNC(4, 384);
        if (tid < 200) {
            const unsigned vals[4] = {(unsigned)iv.x, (unsigned)iv.y, (unsigned)iv.z, (unsigned)iv.w};
            const int row = tid / 25;
            const uint32_t rb = sbase + OFF_CB + (row >> 1) * 32 + (row & 1) * 4;
            bool badidx = false;
#pragma unroll
            for (int i = 0; i < 4; ++i) {
                badidx |= vals[i] >= (unsigned)kV;
                const unsigned v = min(vals[i], 1007u);
                const uint32_t off = rb + (v >> 4) * 128 + ((v << 2) & 24);
                const uint32_t inc = 1u << (((v << 1) & 16) + ((v & 1) << 3));
                asm volatile("red.shared.add.u32 [%0], %1;" ::"r"(off), "r"(inc) : "memory");
            }
            if (badidx) sts32(sMisc + 8, 1);
        }
        BAR_SYNC(4, 384);
        if (builder) {
            uint4* dst = gC + ((cta >> 5) * kV16 + (tid >> 3)) * 256 + (cta & 31) * 8 + (tid & 7);
            dst[0] = lds128(sbase + OFF_CB + tid * 16);
            if (tid < 120) dst[48 * 256] = lds128(sbase + OFF_CB + (384 + tid) * 16);
        }
        BAR_ARRIVE(1, 416);

        {
            uint32_t ab[8], af[8];
            asm volatile("cp.async.wait_all;" ::: "memory");
            __syncwarp();
            {
                const uint32_t la = sbase + ST_TU + (warp * 16 + (lane & 15)) * 80 + (lane >> 4) * 16;
                asm volatile("ldmatrix.sync.aligned.m8n8.x4.shared.b16 {%0,%1,%2,%3}, [%4];"
                             : "=r"(ab[0]), "=r"(ab[1]), "=r"(ab[2]), "=r"(ab[3]) : "r"(la) : "memory");
                asm volatile("ldmatrix.sync.aligned.m8n8.x4.shared.b16 {%0,%1,%2,%3}, [%4];"
                             : "=r"(ab[4]), "=r"(ab[5]), "=r"(ab[6]), "=r"(ab[7]) : "r"(la + 32) : "memory");
            }
#pragma unroll
            for (int i = 0; i < 8; ++i) af[i] = bf2h(ab[i]);
            bool bad = bf_exceeds<4>(ab[0], ab[1], ab[2], ab[3]) || bf_exceeds<4>(ab[4], ab[5], ab[6], ab[7]);

            float e[12], sv[12];
            uint32_t e2[6];
            uint32_t acc0[24], acc1[24];
            const uint64_t dG = make_desc(sbase + OFF_G, 128, 512);
            const uint32_t cst = sbase + OFF_CST;
            auto issue = [&](uint32_t (&acc)[24], int c) {
                wg_fence();
                mma_h96(acc, af[0], af[1], af[2], af[3], dG + ((c * 6144) >> 4), 0);
                mma_h96(acc, af[4], af[5], af[6], af[7], dG + ((c * 6144 + 256) >> 4), 1);
                wg_commit();
            };
            auto consume = [&](uint32_t (&acc)[24], const uint4& cb, const uint4& ch, bool first) {
                const uint32_t bb[4] = {cb.x, cb.y, cb.z, cb.w}, hh[4] = {ch.x, ch.y, ch.z, ch.w};
#pragma unroll
                for (int ai = 0; ai < 4; ++ai) {
#pragma unroll
                    for (int j = 0; j < 6; ++j)
                        e2[j] = hfma2(hadd2_relu(acc[ai * 6 + j], bb[ai]), hh[ai], (first && ai == 0) ? 0u : e2[j]);
                }
            };
            BAR_SYNC(2, 480);
            STAMP(2);
            {
                const int kb = warp & 3, v8 = lane & 7;
                const uint4 tv = lds128(sbase + ST_TV + (v8 + 8 * wg) * 80 + kb * 16);
                const uint32_t wp = sbase + ST_W + (lane >> 3) * 80 + kb * 16;
                const uint32_t gaddr = sbase + OFF_G + (lane >> 3) * 1536 + wg * 512 + kb * 128 + v8 * 16;
                uint4 wr[8];
#pragma unroll
                for (int i = 0; i < 8; ++i) wr[i] = lds128(wp + i * 320);
#pragma unroll
                for (int i = 0; i < 8; ++i)
                    sts128(gaddr + i * 6144, make_uint4(hmul2(tv.x, wr[i].x), hmul2(tv.y, wr[i].y),
                                                        hmul2(tv.z, wr[i].z), hmul2(tv.w, wr[i].w)));
                asm volatile("fence.proxy.async.shared::cta;" ::: "memory");
                BAR_ARRIVE(13, 512);
                BAR_SYNC(14, 480);
                STAMP(13);
            }
            wg_fence();
            mma_n24(sv, ab[0], ab[1], ab[2], ab[3], dG + (49152 >> 4), 0);
            mma_n24(sv, ab[4], ab[5], ab[6], ab[7], dG + ((49152 + 256) >> 4), 1);
            issue(acc0, 0);
            issue(acc1, 1);
            {
                const float mneg = __uint_as_float(lds32(sMisc + 12));
#pragma unroll
                for (int i = 0; i < 12; ++i) e[i] = mneg;
            }
#pragma unroll
            for (int c = 0; c < 8; c += 2) {
                {
                    const uint4 cb = lds128(cst + c * 32), ch = lds128(cst + c * 32 + 16);
                    wg_wait<1>();
                    consume(acc0, cb, ch, (c & 3) == 0);
                    if (c < 6) issue(acc0, c + 2);
                }
                {
                    const uint4 cb = lds128(cst + c * 32 + 32), ch = lds128(cst + c * 32 + 48);
                    if (c < 6) wg_wait<1>(); else wg_wait<0>();
                    consume(acc1, cb, ch, false);
                    if (c < 6) issue(acc1, c + 3);
                }
                if (c & 2) {
#pragma unroll
                    for (int j = 0; j < 6; ++j) { e[2 * j] += h_lo(e2[j]); e[2 * j + 1] += h_hi(e2[j]); }
                }
            }
            const uint32_t tagbits = (lds32(sMisc) + 1) & 3;
            const bool poison = bad || lds32(sMisc + 4) != 0;
            asm volatile("barrier.cluster.wait.acquire.aligned;" ::: "memory");
            float X[12], Y[12];
            float mx = 0.f, ms = 0.f;
#pragma unroll
            for (int i = 0; i < 12; ++i) {
                mx = maxnan_abs(mx, e[i]);
                ms = maxnan_abs(ms, sv[i]);
                X[i] = ex2(e[i]);
                Y[i] = X[i] * sv[i];
            }
            if (tI == (tj >> 2)) {
                const int dv = u - vb0 - 2 * q;
#pragma unroll
                for (int i = 0; i < 12; ++i) {
                    const int th = 8 * (i >> 2) + (i & 1) - 8 * ((i >> 1) & 1);
                    if (dv == th) {
                        const uint32_t dx = (__float_as_uint(X[i]) & ~3u) | tagbits, dy = (__float_as_uint(Y[i]) & ~3u) | tagbits;
                        asm volatile("st.relaxed.gpu.global.v2.u32 [%0], {%1,%2};"
                                     ::"l"(gDiag + u + 8 * ((i >> 1) & 1)), "r"(dx), "r"(dy) : "memory");
                    }
                    X[i] = (dv < th) ? X[i] : 0.f;
                    Y[i] = (dv < th) ? Y[i] : 0.f;
                }
            }
            uint32_t xh[6], yh[6];
#pragma unroll
            for (int j = 0; j < 6; ++j) {
                xh[j] = pack_bf16(X[2 * j], X[2 * j + 1]);
                yh[j] = pack_bf16(Y[2 * j], Y[2 * j + 1]);
            }
            if (!(mx <= 56.f) || !(ms <= 1.0e15f) || (ms != 0.f && ms < 1.0e-15f) || poison) xh[0] = 0x7FC07FC0u;
            const uint32_t b2 = sbase + OFF_B2 + warp * 3072 + rank * 1536;
            const uint32_t dst = b2 + lane * 16;
            asm volatile("stmatrix.sync.aligned.m8n8.x4.trans.shared.b16 [%0], {%1,%2,%3,%4};"
                         ::"r"(dst), "r"(xh[0]), "r"(xh[1]), "r"(xh[2]), "r"(xh[3]) : "memory");
            asm volatile("stmatrix.sync.aligned.m8n8.x4.trans.shared.b16 [%0], {%1,%2,%3,%4};"
                         ::"r"(dst + 512), "r"(xh[4]), "r"(xh[5]), "r"(yh[0]), "r"(yh[1]) : "memory");
            asm volatile("stmatrix.sync.aligned.m8n8.x4.trans.shared.b16 [%0], {%1,%2,%3,%4};"
                         ::"r"(dst + 1024), "r"(yh[2]), "r"(yh[3]), "r"(yh[4]), "r"(yh[5]) : "memory");
            __syncwarp();
            {
                uint32_t rdst, rbar;
                asm volatile("mapa.shared::cluster.u32 %0, %1, %2;" : "=r"(rdst) : "r"(dst), "r"(rank ^ 1));
                asm volatile("mapa.shared::cluster.u32 %0, %1, %2;" : "=r"(rbar) : "r"(sbase + OFF_BAR + 16), "r"(rank ^ 1));
#pragma unroll
                for (int i = 0; i < 3; ++i) {
                    const uint4 v = lds128(dst + i * 512);
                    asm volatile("st.async.weak.shared::cluster.mbarrier::complete_tx::bytes.v4.b32 [%0], {%1,%2,%3,%4}, [%5];"
                                 ::"r"(rdst + i * 512), "r"(v.x), "r"(v.y), "r"(v.z), "r"(v.w), "r"(rbar) : "memory");
                }
            }
        }

        {
            const uint64_t dB = make_desc(sbase + OFF_B2, 128, 256);
            const uint32_t cb0 = sbase + OFF_C + (tid & 127) * 8;
            uint32_t cb = cb0 + wg * 1024;
            uint32_t* pdst = reinterpret_cast<uint32_t*>(gPart) +
                             (((rank * 8 + wg) * 8 + wq * 2 + (r >> 2)) * kTiles + tile) * 16 + (lane & 15);
            uint32_t aA[24], aB[24];
            float acc[48];
            float z0 = 0.f, n0 = 0.f, z1 = 0.f, n1 = 0.f;
            const uint32_t tagbits = (lds32(sMisc) + 1) & 3;

            auto loadA = [&](uint32_t (&a)[24], uint32_t addr) {
#pragma unroll
                for (int s = 0; s < 6; ++s) {
                    const uint2 raw = lds64(addr + s * 4096);
                    a[4 * s + 0] = cnt2bf<0x4140>(raw.x);
                    a[4 * s + 1] = cnt2bf<0x4140>(raw.y);
                    a[4 * s + 2] = cnt2bf<0x4342>(raw.x);
                    a[4 * s + 3] = cnt2bf<0x4342>(raw.y);
                }
            };
            auto mmas = [&](uint32_t (&a)[24], int h) {
                wg_fence();
#pragma unroll
                for (int s = 0; s < 6; ++s)
                    mma_n96(acc, a[4 * s], a[4 * s + 1], a[4 * s + 2], a[4 * s + 3], dB + (((h * 6 + s) * 3072) >> 4),
                            !(h == 0 && s == 0));
                wg_commit();
            };
            auto flush = [&](uint32_t* p) {
                const bool odd = q & 1;
                float s0 = odd ? z0 : n0, k0 = odd ? n0 : z0;
                float s1 = odd ? z1 : n1, k1 = odd ? n1 : z1;
                k0 += __shfl_xor_sync(0xffffffffu, s0, 1);
                k1 += __shfl_xor_sync(0xffffffffu, s1, 1);
                const bool hi = q & 2;
                float s2 = hi ? k0 : k1, k2 = hi ? k1 : k0;
                k2 += __shfl_xor_sync(0xffffffffu, s2, 2);
                const uint32_t val = (__float_as_uint(k2) & ~3u) | tagbits;
                asm volatile("st.relaxed.gpu.global.u32 [%0], %1;" ::"l"(p), "r"(val) : "memory");
            };

            STAMP(3);
            mbar_wait(sbase + OFF_BAR, 0);
            STAMP(4);
            loadA(aA, cb);
            asm volatile("fence.proxy.async.shared::cta;" ::: "memory");
            BAR_SYNC(4, 384);
            mbar_wait_cluster(sbase + OFF_BAR + 16, 0);
            asm volatile("fence.proxy.async.shared::cta;" ::: "memory");
            STAMP(11);
            const int nblk = wg < 2 ? 3 : 2;
#pragma unroll 1
            for (int it = 0; it < nblk; ++it) {
                mmas(aA, 0);
                if (it > 0) flush(pdst - 3 * 8 * kTiles * 16);
                loadA(aB, cb + 24576);
                mmas(aB, 1);
                float c0[12], c1[12];
#pragma unroll
                for (int t = 0; t < 3; ++t) {
                    const uint2 raw = lds64(cb + 49152 + t * 4096);
                    c0[4 * t + 0] = cnt2f<0x7440>(raw.x); c0[4 * t + 1] = cnt2f<0x7441>(raw.x);
                    c0[4 * t + 2] = cnt2f<0x7442>(raw.x); c0[4 * t + 3] = cnt2f<0x7443>(raw.x);
                    c1[4 * t + 0] = cnt2f<0x7440>(raw.y); c1[4 * t + 1] = cnt2f<0x7441>(raw.y);
                    c1[4 * t + 2] = cnt2f<0x7442>(raw.y); c1[4 * t + 3] = cnt2f<0x7443>(raw.y);
                }
                wg_wait<1>();
                const int nxt = wg + 3 * it + 3;
                const uint32_t cbn = cb0 + (nxt >> 2) * kQuart + (nxt & 3) * 1024;
                if (it + 1 < nblk) {
                    mbar_wait(sbase + OFF_BAR + (nxt >> 2) * 8, 0);
                    loadA(aA, cbn);
                } else {
                    BAR_ARRIVE(3, 512);
                }
                wg_wait<0>();
                float za = 0.f, zb = 0.f, zc = 0.f, zd = 0.f, na = 0.f, nb = 0.f, nc = 0.f, nd = 0.f;
#pragma unroll
                for (int vb = 0; vb < 6; ++vb) {
                    const int xb = ((vb / 3) * 6 + vb % 3) * 4, yb = xb + 12;
                    za = fmaf(acc[xb + 0], c0[2 * vb], za);
                    zb = fmaf(acc[xb + 1], c0[2 * vb + 1], zb);
                    zc = fmaf(acc[xb + 2], c1[2 * vb], zc);
                    zd = fmaf(acc[xb + 3], c1[2 * vb + 1], zd);
                    na = fmaf(acc[yb + 0], c0[2 * vb], na);
                    nb = fmaf(acc[yb + 1], c0[2 * vb + 1], nb);
                    nc = fmaf(acc[yb + 2], c1[2 * vb], nc);
                    nd = fmaf(acc[yb + 3], c1[2 * vb + 1], nd);
                }
                z0 = za + zb; z1 = zc + zd; n0 = na + nb; n1 = nc + nd;
                cb = cbn;
                pdst += 3 * 8 * kTiles * 16;
            }
            flush(pdst - 3 * 8 * kTiles * 16);
            STAMP(5);
            if (wg == 2) {
              BAR_SYNC(15, 256);
              if (builder) {
                const int t = tid - 256;
                const uint4 d0 = lds128(sbase + OFF_DUP + t * 32), d1 = lds128(sbase + OFF_DUP + t * 32 + 16);
                const uint32_t dv[7] = {d0.x, d0.y, d0.z, d0.w, d1.x, d1.y, d1.z};
                float zs, ns;
                for (int spin = 0; spin < (1 << 20); ++spin) {
                    uint32_t dx[7], dy[7];
#pragma unroll
                    for (int i = 0; i < 7; ++i) {
                        dx[i] = 0; dy[i] = 0;
                        asm volatile("{\n.reg .pred p;\nsetp.ge.u32 p, %3, 0x20000;\n"
                                     "@p ld.relaxed.gpu.global.v2.u32 {%0,%1}, [%2];\n}\n"
                                     : "+r"(dx[i]), "+r"(dy[i]) : "l"(gDiag + (dv[i] & 1023)), "r"(dv[i]) : "memory");
                    }
                    uint32_t bad = 0;
                    zs = 0.f; ns = 0.f;
#pragma unroll
                    for (int i = 0; i < 7; ++i) {
                        const bool dup = dv[i] >= 0x20000u;
                        bad |= dup ? ((dx[i] ^ tagbits) | (dy[i] ^ tagbits)) & 3u : 0u;
                        const float cc = 0.5f * (float)((dv[i] >> 16) - 1);
                        zs = dup ? fmaf(cc, __uint_as_float(dx[i] & ~3u), zs) : zs;
                        ns = dup ? fmaf(cc, __uint_as_float(dy[i] & ~3u), ns) : ns;
                    }
                    if (!__any_sync(0xffffffffu, bad != 0)) break;
                }
#pragma unroll
                for (int o = 1; o < 16; o <<= 1) {
                    zs += __shfl_xor_sync(0xffffffffu, zs, o);
                    ns += __shfl_xor_sync(0xffffffffu, ns, o);
                }
                if ((lane & 15) == 0) sts64(sbase + OFF_RED + 256 + (t >> 4) * 8, __float_as_uint(zs), __float_as_uint(ns));
              }
              BAR_ARRIVE(12, 256);
            }
        }
        BAR_SYNC(5, 512);
        if (builder && lds32(sMisc + 8) != 0) fallback_rows(idx, table, ii, jj, W, bv, hv, pv, out, smem, cta * 8, tid);
    }
}

}

extern "C" void kernel_launch(void* const* d_in, const int* in_sizes, int n_in, void* d_out, int out_size) {
    (void)in_sizes; (void)n_in; (void)out_size;
    static bool init_done = false;
    static bool fits = false;
    static void *pC = nullptr, *pPart = nullptr, *pCnt = nullptr, *pDiag = nullptr;
    static TileMap tmap;
    if (!init_done) {
        int n = 0;
        for (int j = 0; j < 21; ++j)
            for (int I = 0; I <= j / 4; ++I) tmap.v[n++] = (unsigned char)((I << 5) | j);
        cudaFuncSetAttribute(afm_kernel, cudaFuncAttributeMaxDynamicSharedMemorySize, SMEM_BYTES);
        cudaGetSymbolAddress(&pC, g_C);
        cudaGetSymbolAddress(&pPart, g_part);
        cudaGetSymbolAddress(&pCnt, g_cnt);
        cudaGetSymbolAddress(&pDiag, g_diag);
        cudaLaunchConfig_t cfg = {};
        cfg.gridDim = dim3(kGrid);
        cfg.blockDim = dim3(kThreads);
        cfg.dynamicSmemBytes = SMEM_BYTES;
        cudaLaunchAttribute at;
        at.id = cudaLaunchAttributeClusterDimension;
        at.val.clusterDim.x = 2; at.val.clusterDim.y = 1; at.val.clusterDim.z = 1;
        cfg.attrs = &at;
        cfg.numAttrs = 1;
        int ncl = 0;
        fits = cudaOccupancyMaxActiveClusters(&ncl, afm_kernel, &cfg) == cudaSuccess && ncl >= kTiles;
        (void)cudaGetLastError();
        init_done = true;
    }
    const int* idx = (const int*)d_in[0];
    const __nv_bfloat16* table = (const __nv_bfloat16*)d_in[1];
    const int* ii = (const int*)d_in[2];
    const int* jj = (const int*)d_in[3];
    const __nv_bfloat16* W = (const __nv_bfloat16*)d_in[4];
    const __nv_bfloat16* b = (const __nv_bfloat16*)d_in[5];
    const __nv_bfloat16* h = (const __nv_bfloat16*)d_in[6];
    const __nv_bfloat16* p = (const __nv_bfloat16*)d_in[7];
    if (fits) {
        afm_kernel<<<kGrid, kThreads, SMEM_BYTES>>>(idx, table, ii, jj, W, b, h, p, (__nv_bfloat16*)d_out,
                                                    (uint4*)pC, (uint4*)pPart, (uint2*)pDiag, (unsigned*)pCnt, tmap);
    } else {
        afm_direct_kernel<<<128, 384>>>(idx, table, ii, jj, W, b, h, p, (__nv_bfloat16*)d_out);
    }
}
```

```cpp
#include <cuda_runtime.h>
#include <cuda_bf16.h>
#include <stdint.h>

namespace {

constexpr int kF = 100, kD = 32, kV = 1000, kP = 4950;
constexpr int kV16 = 63;
constexpr int kTiles = 66;
constexpr int kGrid = 132;
constexpr int kThreads = 512;
constexpr int kQuart = 61440;

constexpr int OFF_C = 0;
constexpr int OFF_B2 = OFF_C + 2 * kQuart;
constexpr int OFF_G = OFF_B2 + 36864;
constexpr int OFF_CB = OFF_G + 50688;
constexpr int OFF_CST = OFF_CB + 8064;
constexpr int OFF_BAR = OFF_CST + 256;
constexpr int OFF_MISC = OFF_BAR + 64;
constexpr int SMEM_BYTES = OFF_MISC + 64;
constexpr int ST_TU = OFF_C;
constexpr int ST_TV = ST_TU + 15360;
constexpr int ST_W = ST_TV + 1920;

__device__ uint4 g_C[16 * kV16 * 64];
__device__ uint4 g_part[128 * kTiles * 4];
__device__ uint2 g_diag[1024];
__device__ unsigned g_cnt[5 * 32];


__device__ __forceinline__ uint32_t smem_u32(const void* p) {
    return (uint32_t)__cvta_generic_to_shared(p);
}
__device__ __forceinline__ uint64_t make_desc(uint32_t addr, uint32_t lbo, uint32_t sbo) {
    return (uint64_t)((addr & 0x3FFFF) >> 4) | ((uint64_t)(lbo >> 4) << 16) | ((uint64_t)(sbo >> 4) << 32);
}
__device__ __forceinline__ void wg_fence() { asm volatile("wgmma.fence.sync.aligned;" ::: "memory"); }
__device__ __forceinline__ void wg_commit() { asm volatile("wgmma.commit_group.sync.aligned;" ::: "memory"); }
template <int N>
__device__ __forceinline__ void wg_wait() { asm volatile("wgmma.wait_group.sync.aligned %0;" ::"n"(N) : "memory"); }

__device__ __forceinline__ void mma_n24(float (&d)[12], uint32_t a0, uint32_t a1, uint32_t a2, uint32_t a3,
                                        uint64_t desc, int scale_d) {
    asm volatile(
        "{\n.reg .pred p;\nsetp.ne.b32 p, %17, 0;\n"
        "wgmma.mma_async.sync.aligned.m64n24k16.f32.bf16.bf16 "
        "{%0,%1,%2,%3,%4,%5,%6,%7,%8,%9,%10,%11},"
        "{%12,%13,%14,%15}, %16, p, 1, 1, 0;\n}\n"
        : "+f"(d[0]), "+f"(d[1]), "+f"(d[2]), "+f"(d[3]), "+f"(d[4]), "+f"(d[5]), "+f"(d[6]), "+f"(d[7]),
          "+f"(d[8]), "+f"(d[9]), "+f"(d[10]), "+f"(d[11])
        : "r"(a0), "r"(a1), "r"(a2), "r"(a3), "l"(desc), "r"(scale_d));
}

__device__ __forceinline__ void mma_h96(uint32_t (&d)[24], uint32_t a0, uint32_t a1, uint32_t a2, uint32_t a3,
                                        uint64_t desc, int scale_d) {
    asm volatile(
        "{\n.reg .pred p;\nsetp.ne.b32 p, %29, 0;\n"
        "wgmma.mma_async.sync.aligned.m64n96k16.f16.f16.f16 "
        "{%0,%1,%2,%3,%4,%5,%6,%7,%8,%9,%10,%11,%12,%13,%14,%15,%16,%17,%18,%19,%20,%21,%22,%23},"
        "{%24,%25,%26,%27}, %28, p, 1, 1, 0;\n}\n"
        : "+r"(d[0]), "+r"(d[1]), "+r"(d[2]), "+r"(d[3]), "+r"(d[4]), "+r"(d[5]), "+r"(d[6]), "+r"(d[7]),
          "+r"(d[8]), "+r"(d[9]), "+r"(d[10]), "+r"(d[11]), "+r"(d[12]), "+r"(d[13]), "+r"(d[14]), "+r"(d[15]),
          "+r"(d[16]), "+r"(d[17]), "+r"(d[18]), "+r"(d[19]), "+r"(d[20]), "+r"(d[21]), "+r"(d[22]), "+r"(d[23])
        : "r"(a0), "r"(a1), "r"(a2), "r"(a3), "l"(desc), "r"(scale_d));
}

__device__ __forceinline__ void mma_n96(float (&d)[48], uint32_t a0, uint32_t a1, uint32_t a2, uint32_t a3,
                                        uint64_t desc, int scale_d) {
    asm volatile(
        "{\n.reg .pred p;\nsetp.ne.b32 p, %53, 0;\n"
        "wgmma.mma_async.sync.aligned.m64n96k16.f32.bf16.bf16 "
        "{%0,%1,%2,%3,%4,%5,%6,%7,%8,%9,%10,%11,%12,%13,%14,%15,%16,%17,%18,%19,%20,%21,%22,%23,"
        "%24,%25,%26,%27,%28,%29,%30,%31,%32,%33,%34,%35,%36,%37,%38,%39,%40,%41,%42,%43,%44,%45,%46,%47},"
        "{%48,%49,%50,%51}, %52, p, 1, 1, 0;\n}\n"
        : "+f"(d[0]), "+f"(d[1]), "+f"(d[2]), "+f"(d[3]), "+f"(d[4]), "+f"(d[5]), "+f"(d[6]), "+f"(d[7]),
          "+f"(d[8]), "+f"(d[9]), "+f"(d[10]), "+f"(d[11]), "+f"(d[12]), "+f"(d[13]), "+f"(d[14]), "+f"(d[15]),
          "+f"(d[16]), "+f"(d[17]), "+f"(d[18]), "+f"(d[19]), "+f"(d[20]), "+f"(d[21]), "+f"(d[22]), "+f"(d[23]),
          "+f"(d[24]), "+f"(d[25]), "+f"(d[26]), "+f"(d[27]), "+f"(d[28]), "+f"(d[29]), "+f"(d[30]), "+f"(d[31]),
          "+f"(d[32]), "+f"(d[33]), "+f"(d[34]), "+f"(d[35]), "+f"(d[36]), "+f"(d[37]), "+f"(d[38]), "+f"(d[39]),
          "+f"(d[40]), "+f"(d[41]), "+f"(d[42]), "+f"(d[43]), "+f"(d[44]), "+f"(d[45]), "+f"(d[46]), "+f"(d[47])
        : "r"(a0), "r"(a1), "r"(a2), "r"(a3), "l"(desc), "r"(scale_d));
}

__device__ __forceinline__ uint32_t bmul2(uint32_t a, uint32_t b) {
    uint32_t r;
    asm("mul.rn.bf16x2 %0, %1, %2;" : "=r"(r) : "r"(a), "r"(b));
    return r;
}
__device__ __forceinline__ uint32_t pack_bf16(float lo, float hi) {
    uint32_t r;
    asm("cvt.rn.bf16x2.f32 %0, %1, %2;" : "=r"(r) : "f"(hi), "f"(lo));
    return r;
}
__device__ __forceinline__ float bf_lo(uint32_t x) { return __uint_as_float(x << 16); }
__device__ __forceinline__ float bf_hi(uint32_t x) { return __uint_as_float(x & 0xffff0000u); }
__device__ __forceinline__ uint32_t pack_f16(float lo, float hi) {
    uint32_t r;
    asm("cvt.rn.f16x2.f32 %0, %1, %2;" : "=r"(r) : "f"(hi), "f"(lo));
    return r;
}
__device__ __forceinline__ uint32_t bf2h(uint32_t x) { return pack_f16(bf_lo(x), bf_hi(x)); }
__device__ __forceinline__ uint32_t hmul2(uint32_t a, uint32_t b) {
    uint32_t r;
    asm("mul.rn.f16x2 %0, %1, %2;" : "=r"(r) : "r"(a), "r"(b));
    return r;
}
__device__ __forceinline__ uint32_t hfma2(uint32_t a, uint32_t b, uint32_t c) {
    uint32_t r;
    asm("fma.rn.f16x2 %0, %1, %2, %3;" : "=r"(r) : "r"(a), "r"(b), "r"(c));
    return r;
}
__device__ __forceinline__ uint32_t hadd2_relu(uint32_t a, uint32_t c) {
    uint32_t r;
    asm("fma.rn.relu.f16x2 %0, %1, %2, %3;" : "=r"(r) : "r"(a), "r"(0x3C003C00u), "r"(c));
    return r;
}
__device__ __forceinline__ float h_lo(uint32_t x) {
    float r;
    asm("{.reg .f16 l, h; mov.b32 {l, h}, %1; cvt.f32.f16 %0, l;}" : "=f"(r) : "r"(x));
    return r;
}
__device__ __forceinline__ float h_hi(uint32_t x) {
    float r;
    asm("{.reg .f16 l, h; mov.b32 {l, h}, %1; cvt.f32.f16 %0, h;}" : "=f"(r) : "r"(x));
    return r;
}
template <int LOG2>
__device__ __forceinline__ bool bf_exceeds(uint32_t a, uint32_t b, uint32_t c, uint32_t d) {
    const uint32_t m = 0x7fff7fffu;
    const uint32_t mx = __vmaxu2(__vmaxu2(a & m, b & m), __vmaxu2(c & m, d & m));
    return __vcmpgtu2(mx, ((127u + LOG2) << 7) * 0x10001u) != 0;
}
__device__ __forceinline__ float ex2(float x) {
    float r;
    asm("ex2.approx.ftz.f32 %0, %1;" : "=f"(r) : "f"(x));
    return r;
}
__device__ __forceinline__ float maxnan_abs(float m, float x) {
    float r;
    asm("max.NaN.f32 %0, %1, %2;" : "=f"(r) : "f"(m), "f"(fabsf(x)));
    return r;
}
__device__ __forceinline__ uint4 lds128(uint32_t a) {
    uint4 v;
    asm volatile("ld.shared.v4.u32 {%0,%1,%2,%3}, [%4];" : "=r"(v.x), "=r"(v.y), "=r"(v.z), "=r"(v.w) : "r"(a));
    return v;
}
__device__ __forceinline__ uint2 lds64(uint32_t a) {
    uint2 v;
    asm volatile("ld.shared.v2.u32 {%0,%1}, [%2];" : "=r"(v.x), "=r"(v.y) : "r"(a));
    return v;
}
__device__ __forceinline__ uint32_t lds32(uint32_t a) {
    uint32_t v;
    asm volatile("ld.shared.u32 %0, [%1];" : "=r"(v) : "r"(a) : "memory");
    return v;
}
__device__ __forceinline__ uint32_t lds32_nv(uint32_t a) {
    uint32_t v;
    asm("ld.shared.u32 %0, [%1];" : "=r"(v) : "r"(a));
    return v;
}
__device__ __forceinline__ uint32_t opaque(uint32_t a) {
    asm volatile("" : "+r"(a) :: "memory");
    return a;
}
__device__ __forceinline__ void sts128(uint32_t a, uint4 v) {
    asm volatile("st.shared.v4.u32 [%0], {%1,%2,%3,%4};" ::"r"(a), "r"(v.x), "r"(v.y), "r"(v.z), "r"(v.w) : "memory");
}
__device__ __forceinline__ void sts16(uint32_t a, uint32_t x) {
    asm volatile("st.shared.u16 [%0], %1;" ::"r"(a), "h"((unsigned short)x) : "memory");
}
__device__ __forceinline__ void sts32(uint32_t a, uint32_t x) {
    asm volatile("st.shared.u32 [%0], %1;" ::"r"(a), "r"(x) : "memory");
}
__device__ __forceinline__ void mbar_wait(uint32_t bar, uint32_t parity) {
    uint32_t done = 0;
    for (int it = 0; it < (1 << 20) && !done; ++it) {
        asm volatile(
            "{\n.reg .pred p;\nmbarrier.try_wait.parity.shared::cta.b64 p, [%1], %2;\nselp.u32 %0, 1, 0, p;\n}\n"
            : "=r"(done) : "r"(bar), "r"(parity) : "memory");
    }
}
__device__ __forceinline__ void mbar_wait_cluster(uint32_t bar, uint32_t parity) {
    uint32_t done = 0;
    for (int it = 0; it < (1 << 20) && !done; ++it) {
        asm volatile(
            "{\n.reg .pred p;\nmbarrier.try_wait.parity.acquire.cluster.shared::cta.b64 p, [%1], %2;\nselp.u32 %0, 1, 0, p;\n}\n"
            : "=r"(done) : "r"(bar), "r"(parity) : "memory");
    }
}
__device__ __forceinline__ void cp16(uint32_t dst, const void* src, bool valid) {
    asm volatile("cp.async.cg.shared.global [%0], [%1], 16, %2;" ::"r"(dst), "l"(src), "r"(valid ? 16 : 0) : "memory");
}
#define BAR_SYNC(id, n) asm volatile("bar.sync " #id ", " #n ";" ::: "memory")
#define BAR_ARRIVE(id, n) asm volatile("bar.arrive " #id ", " #n ";" ::: "memory")
template <int SEL>
__device__ __forceinline__ uint32_t cnt2bf(uint32_t w) {
    uint32_t r;
    asm volatile("{\n.reg .b32 t;\nprmt.b32 t, %1, 0x43434343, %2;\nadd.rn.bf16x2 %0, t, %3;\n}\n"
                 : "=r"(r) : "r"(w), "n"(SEL), "r"(0xC300C300u));
    return r;
}
template <int SEL>
__device__ __forceinline__ float cnt2f(uint32_t w) {
    float r;
    asm volatile("{\n.reg .b32 t;\nprmt.b32 t, %1, 0x4B000000, %2;\nadd.rn.f32 %0, t, 0fCB000000;\n}\n"
                 : "=f"(r) : "r"(w), "n"(SEL));
    return r;
}

__device__ __noinline__ void fallback_rows(const int* __restrict__ idx, const __nv_bfloat16* __restrict__ table,
                                           const int* __restrict__ ii, const int* __restrict__ jj,
                                           const __nv_bfloat16* __restrict__ W, const __nv_bfloat16* __restrict__ bv,
                                           const __nv_bfloat16* __restrict__ hv, const __nv_bfloat16* __restrict__ pv,
                                           __nv_bfloat16* __restrict__ out, unsigned char* smem, int b0, int tid) {
    float* sW = reinterpret_cast<float*>(smem);
    float* sb = sW + 1024;
    float* sh = sb + 32;
    float* sp = sh + 32;
    float* sE = sp + 32;
    float* sR = sE + kF * 33;
    for (int i = tid; i < 1024; i += 384) sW[i] = __bfloat162float(W[i]);
    if (tid < 32) {
        sb[tid] = __bfloat162float(bv[tid]);
        sh[tid] = __bfloat162float(hv[tid]);
        sp[tid] = __bfloat162float(pv[tid]);
    }
    for (int r = 0; r < 8; ++r) {
        const int b = b0 + r;
        BAR_SYNC(6, 384);
        for (int i = tid; i < kF * kD; i += 384) {
            int f = i >> 5, d = i & 31;
            int v = idx[b * kF + f];
            if (v < 0) v += kV;
            v = min(max(v, 0), kV - 1);
            sE[f * 33 + d] = __bfloat162float(table[v * kD + d]);
        }
        BAR_SYNC(6, 384);
        float m = -INFINITY, z = 0.f, n = 0.f;
        for (int k = tid; k < kP; k += 384) {
            int i = ii[k], j = jj[k];
            if (i < 0) i += kF;
            if (j < 0) j += kF;
            i = min(max(i, 0), kF - 1);
            j = min(max(j, 0), kF - 1);
            float hid[32];
#pragma unroll
            for (int a = 0; a < 32; ++a) hid[a] = sb[a];
            float s = 0.f;
            for (int d = 0; d < 32; ++d) {
                float pr = __bfloat162float(__float2bfloat16(sE[i * 33 + d] * sE[j * 33 + d]));
                s = fmaf(pr, sp[d], s);
#pragma unroll
                for (int a = 0; a < 32; a += 4) {
                    float4 w = *reinterpret_cast<const float4*>(sW + d * 32 + a);
                    hid[a] = fmaf(pr, w.x, hid[a]);
                    hid[a + 1] = fmaf(pr, w.y, hid[a + 1]);
                    hid[a + 2] = fmaf(pr, w.z, hid[a + 2]);
                    hid[a + 3] = fmaf(pr, w.w, hid[a + 3]);
                }
            }
            float e = 0.f;
#pragma unroll
            for (int a = 0; a < 32; ++a) e = fmaf(0.5f * (hid[a] + fabsf(hid[a])), sh[a], e);
            float mn = fmaxf(m, e);
            float c = __expf(m - mn), w = __expf(e - mn);
            if (m == -INFINITY) c = 0.f;
            z = z * c + w;
            n = n * c + w * s;
            m = mn;
        }
#pragma unroll
        for (int o = 16; o > 0; o >>= 1) {
            float m2 = __shfl_xor_sync(0xffffffffu, m, o);
            float z2 = __shfl_xor_sync(0xffffffffu, z, o);
            float n2 = __shfl_xor_sync(0xffffffffu, n, o);
            float mn = fmaxf(m, m2);
            float c1 = (m == -INFINITY) ? 0.f : __expf(m - mn);
            float c2 = (m2 == -INFINITY) ? 0.f : __expf(m2 - mn);
            z = z * c1 + z2 * c2;
            n = n * c1 + n2 * c2;
            m = mn;
        }
        if ((tid & 31) == 0) {
            sR[(tid >> 5) * 3 + 0] = m;
            sR[(tid >> 5) * 3 + 1] = z;
            sR[(tid >> 5) * 3 + 2] = n;
        }
        BAR_SYNC(6, 384);
        if (tid == 0) {
            float mm = -INFINITY;
            for (int w = 0; w < 12; ++w) mm = fmaxf(mm, sR[w * 3]);
            float zz = 0.f, nn = 0.f;
            for (int w = 0; w < 12; ++w) {
                float c = (sR[w * 3] == -INFINITY) ? 0.f : __expf(sR[w * 3] - mm);
                zz += sR[w * 3 + 1] * c;
                nn += sR[w * 3 + 2] * c;
            }
            out[b] = __float2bfloat16(nn / zz);
        }
    }
}

__global__ void __launch_bounds__(384, 1)
afm_direct_kernel(const int* __restrict__ idx, const __nv_bfloat16* __restrict__ table,
                  const int* __restrict__ ii, const int* __restrict__ jj,
                  const __nv_bfloat16* __restrict__ W, const __nv_bfloat16* __restrict__ bv,
                  const __nv_bfloat16* __restrict__ hv, const __nv_bfloat16* __restrict__ pv,
                  __nv_bfloat16* __restrict__ out) {
    __shared__ __align__(16) unsigned char sm[18432];
    fallback_rows(idx, table, ii, jj, W, bv, hv, pv, out, sm, blockIdx.x * 8, threadIdx.x);
}

__global__ void __cluster_dims__(2, 1, 1) __launch_bounds__(kThreads, 1)
afm_kernel(const int* __restrict__ idx, const __nv_bfloat16* __restrict__ table,
           const int* __restrict__ ii, const int* __restrict__ jj,
           const __nv_bfloat16* __restrict__ W, const __nv_bfloat16* __restrict__ bv,
           const __nv_bfloat16* __restrict__ hv, const __nv_bfloat16* __restrict__ pv,
           __nv_bfloat16* __restrict__ out, uint4* __restrict__ gC, uint4* __restrict__ gPart,
           uint2* __restrict__ gDiag, unsigned* __restrict__ gCnt) {
    extern __shared__ __align__(1024) unsigned char smem[];
    const uint32_t sbase = smem_u32(smem);
    const int T = threadIdx.x;
    const int lane = T & 31;
    const int cta = blockIdx.x;
    const int tile = cta >> 1, rank = cta & 1;
    const bool builder = cta < 128;

    const int tm = (tile >= 4) + (tile >= 12) + (tile >= 24) + (tile >= 40) + (tile >= 60);
    const int trem = tile - 2 * tm * (tm + 1);
    const int trr = (trem >= tm + 1) + (trem >= 2 * (tm + 1)) + (trem >= 3 * (tm + 1));
    const int tI = trem - trr * (tm + 1), tj = 4 * tm + trr;
    const int vb0 = tj * 48 + rank * 24;
    const float kLog2e = 1.44269504088896340736f;
    const uint32_t sMisc = sbase + OFF_MISC;

    if (T < 128) {
        asm volatile("setmaxnreg.dec.sync.aligned.u32 56;");
        const int t = T;
        unsigned* myCnt = gCnt + (cta >> 5) * 32;
        const int j = t - 32;
        uint4 y4 = make_uint4(0, 0, 0, 0), y5 = y4, z4 = y4, p4 = y4;
        if (t >= 32) {
            y4 = __ldg(reinterpret_cast<const uint4*>(W) + j);
            if (j < 32) y5 = __ldg(reinterpret_cast<const uint4*>(W) + 96 + j);
            if (vb0 + (j >> 2) < kV) z4 = __ldg(reinterpret_cast<const uint4*>(table + (vb0 + (j >> 2)) * kD) + (j & 3));
            p4 = __ldg(reinterpret_cast<const uint4*>(pv) + (j & 3));
        }
        uint32_t x0 = 0, x1 = 0, x2 = 0, x3 = 0;
        if (t >= 64) {
            const int kc = min(cta * 38 + (t - 64), kP - 1), kp = max(kc - 1, 0);
            x0 = __ldg(ii + kc); x1 = __ldg(jj + kc); x2 = __ldg(ii + kp); x3 = __ldg(jj + kp);
        } else if (t >= 32) {
            x0 = __ldg(reinterpret_cast<const unsigned short*>(bv) + lane);
            x1 = __ldg(reinterpret_cast<const unsigned short*>(hv) + lane);
        }
        if (t == 0) {
            asm volatile("ld.relaxed.gpu.global.u32 %0, [%1];" : "=r"(x0) : "l"(myCnt) : "memory");
#pragma unroll
            for (int i = 0; i < 3; ++i)
                asm volatile("mbarrier.init.shared::cta.b64 [%0], 1;" ::"r"(sbase + OFF_BAR + i * 8) : "memory");
            const uint32_t qbytes = min(12, kV16 - tI * 12) * 4096 + 12288;
            asm volatile("mbarrier.arrive.expect_tx.shared::cta.b64 _, [%0], %1;" ::"r"(sbase + OFF_BAR), "r"(qbytes) : "memory");
            asm volatile("mbarrier.arrive.expect_tx.shared::cta.b64 _, [%0], %1;" ::"r"(sbase + OFF_BAR + 8), "r"(qbytes) : "memory");
            asm volatile("mbarrier.arrive.expect_tx.shared::cta.b64 _, [%0], %1;" ::"r"(sbase + OFF_BAR + 16), "r"(18432) : "memory");
            asm volatile("fence.mbarrier_init.release.cluster;" ::: "memory");
        }
        if (t == 32) sts32(sMisc + 4, 0);
        __syncwarp();
        asm volatile("barrier.cluster.arrive.relaxed.aligned;" ::: "memory");
        BAR_SYNC(7, 128);
        if (t < 32) {
            if (t == 0) sts32(sMisc, builder ? (x0 >> 5) : (x0 >> 2));
            __syncwarp();
            BAR_ARRIVE(14, 512);
            BAR_SYNC(1, 416);
            if (t == 0) asm volatile("red.release.gpu.global.add.u32 [%0], 1;" ::"l"(myCnt) : "memory");
        } else {
            auto put_wt = [&](const uint4& y, int c) {
                const uint32_t wt = sbase + ST_W + (c & 3) * 640 + (c >> 2) * 2;
                const uint32_t w0 = bf2h(y.x), w1 = bf2h(y.y), w2 = bf2h(y.z), w3 = bf2h(y.w);
                sts16(wt, w0); sts16(wt + 80, w0 >> 16); sts16(wt + 160, w1); sts16(wt + 240, w1 >> 16);
                sts16(wt + 320, w2); sts16(wt + 400, w2 >> 16); sts16(wt + 480, w3); sts16(wt + 560, w3 >> 16);
            };
            sts128(sbase + ST_TV + (j >> 2) * 80 + (j & 3) * 16, make_uint4(bf2h(z4.x), bf2h(z4.y), bf2h(z4.z), bf2h(z4.w)));
            put_wt(y4, j);
            if (j < 32) put_wt(y5, 96 + j);
            BAR_ARRIVE(2, 480);
            {
                p4.x = opaque(p4.x); p4.y = opaque(p4.y); p4.z = opaque(p4.z); p4.w = opaque(p4.w);
                const int kb = j & 3, vl = j >> 2;
                sts128(sbase + OFF_G + 49152 + (vl >> 3) * 512 + kb * 128 + (vl & 7) * 16,
                       make_uint4(bmul2(z4.x, p4.x), bmul2(z4.y, p4.y), bmul2(z4.z, p4.z), bmul2(z4.w, p4.w)));
            }
            bool bad = bf_exceeds<3>(y4.x, y4.y, y4.z, y4.w) || bf_exceeds<3>(y5.x, y5.y, y5.z, y5.w) ||
                       bf_exceeds<4>(z4.x, z4.y, z4.z, z4.w);
            if (t < 64) {
                const float bb = __uint_as_float(x0 << 16), hh = __uint_as_float(x1 << 16) * kLog2e;
                sts32(sbase + OFF_CST + (lane >> 2) * 32 + (lane & 3) * 4, pack_f16(bb, bb));
                sts32(sbase + OFF_CST + (lane >> 2) * 32 + 16 + (lane & 3) * 4, pack_f16(hh, hh));
                bad |= !(fabsf(hh) <= 8.f);
                float mm = hh * fmaxf(bb, 0.f);
#pragma unroll
                for (int o = 16; o > 0; o >>= 1) mm += __shfl_xor_sync(0xffffffffu, mm, o);
                if (lane == 0) sts32(sMisc + 12, __float_as_uint(-mm));
            } else {
                const int kk = cta * 38 + (t - 64);
                if (t < 64 + 38 && kk < kP) {
                    const int ci = x0, cj = x1, pi = x2, pj = x3;
                    int ei, ej;
                    if (kk == 0) { ei = 0; ej = 1; }
                    else if (pj + 1 < kF) { ei = pi; ej = pj + 1; }
                    else { ei = pi + 1; ej = pi + 2; }
                    bad |= (ci != ei || cj != ej);
                }
            }
            if (bad) sts32(sMisc + 4, 1);
            asm volatile("fence.proxy.async.shared::cta;" ::: "memory");
            BAR_ARRIVE(14, 512);
        }
        BAR_SYNC(13, 512);
        const unsigned epoch = lds32(sMisc);
        const uint32_t tag = (epoch + 1) & 3;
        if (t < 64) {
            const int w = t >> 5;
            const unsigned target = (epoch + 1) << 5;
            const unsigned* cp = gCnt + (rank * 2 + w) * 32;
            const uint32_t abytes = min(12, kV16 - tI * 12) * 4096;
            const unsigned char* gb = reinterpret_cast<const unsigned char*>(gC) + (rank * 2 + w) * (kV16 * 4096);
            const uint32_t bar = sbase + OFF_BAR + w * 8;
            const uint32_t dst = sbase + OFF_C + w * kQuart;
            if (lane == 0) {
                unsigned c;
                for (int it = 0; it < (1 << 20); ++it) {
                    asm volatile("ld.acquire.gpu.global.u32 %0, [%1];" : "=r"(c) : "l"(cp) : "memory");
                    if ((int)(c - target) >= 0) break;
                }
                asm volatile("fence.proxy.async.global;" ::: "memory");
                asm volatile("cp.async.bulk.shared::cluster.global.mbarrier::complete_tx::bytes [%0], [%1], %2, [%3];"
                             ::"r"(dst), "l"(gb + tI * 49152), "r"(abytes), "r"(bar) : "memory");
                asm volatile("cp.async.bulk.shared::cluster.global.mbarrier::complete_tx::bytes [%0], [%1], %2, [%3];"
                             ::"r"(dst + 49152), "l"(gb + tj * 12288), "r"(12288), "r"(bar) : "memory");
            }
            __syncwarp();
        }
        float dz, dn;
        {
            uint32_t dv[8] = {0, 0, 0, 0, 0, 0, 0, 0};
            if (builder) {
                const int row = t >> 4;
                const int* ip = idx + (cta * 8 + row) * kF + (t & 15);
                unsigned vals[7];
#pragma unroll
                for (int i = 0; i < 7; ++i) vals[i] = __ldg(ip + min(16 * i, 99 - (t & 15)));
                const uint32_t rb = opaque(sbase + OFF_CB + (row >> 1) * 32 + (row & 1) * 4);
#pragma unroll
                for (int i = 0; i < 7; ++i) {
                    const unsigned v = min(vals[i], 1007u);
                    uint32_t c = (lds32_nv(rb + (v >> 4) * 128 + ((v << 2) & 24)) >>
                                  (((v << 1) & 16) + ((v & 1) << 3))) & 0xff;
                    if (i == 6 && (t & 15) >= 4) c = 1;
                    dv[i] = v | (c << 16);
                }
            }
            BAR_SYNC(15, 512);
            for (int spin = 0; spin < (1 << 20); ++spin) {
                uint32_t dx[7], dy[7];
#pragma unroll
                for (int i = 0; i < 7; ++i) {
                    dx[i] = tag; dy[i] = tag;
                    asm volatile("{\n.reg .pred p;\nsetp.ge.u32 p, %3, 0x20000;\n"
                                 "@p ld.relaxed.gpu.global.v2.u32 {%0,%1}, [%2];\n}\n"
                                 : "+r"(dx[i]), "+r"(dy[i]) : "l"(gDiag + (dv[i] & 1023)), "r"(dv[i]) : "memory");
                }
                uint32_t bad = 0;
                dz = 0.f; dn = 0.f;
#pragma unroll
                for (int i = 0; i < 7; ++i) {
                    bad |= (dx[i] ^ tag) | (dy[i] ^ tag);
                    const float cc = 0.5f * (float)((int)(dv[i] >> 16) - 1);
                    dz = fmaf(cc, __uint_as_float(dx[i] & ~3u), dz);
                    dn = fmaf(cc, __uint_as_float(dy[i] & ~3u), dn);
                }
                if (!__any_sync(0xffffffffu, (bad & 3u) != 0)) break;
                __nanosleep(200);
            }
#pragma unroll
            for (int o = 1; o < 16; o <<= 1) {
                dz += __shfl_xor_sync(0xffffffffu, dz, o);
                dn += __shfl_xor_sync(0xffffffffu, dn, o);
            }
            dz = __shfl_sync(0xffffffffu, dz, (lane & 1) * 16);
            dn = __shfl_sync(0xffffffffu, dn, (lane & 1) * 16);
        }
        if (!builder) BAR_SYNC(12, 256);
        if (builder) {
            const uint4* src = gPart + (size_t)cta * (kTiles * 4) + lane * 4 + (t >> 5);
            auto ld = [&](uint4& v, const uint4* ptr, uint32_t on) {
                asm volatile("{\n.reg .pred p;\nsetp.ne.u32 p, %5, 0;\n"
                             "@p ld.relaxed.gpu.global.v4.u32 {%0,%1,%2,%3}, [%4];\n}\n"
                             : "+r"(v.x), "+r"(v.y), "+r"(v.z), "+r"(v.w) : "l"(ptr), "r"(on) : "memory");
            };
            auto stale = [&](const uint4& v) { return ((v.x ^ tag) | (v.y ^ tag) | (v.z ^ tag) | (v.w ^ tag)) & 3u; };
            uint4 a0 = make_uint4(~tag, 0, 0, 0), a1 = a0, a2 = a0;
            if (lane >= kTiles - 64) a2 = make_uint4(tag, tag, tag, tag);
            uint32_t p0 = 1, p1 = 1, p2 = stale(a2);
            for (int spin = 0; spin < (1 << 20); ++spin) {
                ld(a0, src, p0); ld(a1, src + 128, p1); ld(a2, src + 256, p2);
                p0 = stale(a0); p1 = stale(a1); p2 = stale(a2);
                if (spin == 0) BAR_SYNC(12, 256);
                if (!__any_sync(0xffffffffu, (p0 | p1 | p2) != 0)) break;
            }
            float s0 = __uint_as_float(a0.x & ~3u) + __uint_as_float(a1.x & ~3u) + __uint_as_float(a2.x & ~3u);
            float s1 = __uint_as_float(a0.y & ~3u) + __uint_as_float(a1.y & ~3u) + __uint_as_float(a2.y & ~3u);
            float s2 = __uint_as_float(a0.z & ~3u) + __uint_as_float(a1.z & ~3u) + __uint_as_float(a2.z & ~3u);
            float s3 = __uint_as_float(a0.w & ~3u) + __uint_as_float(a1.w & ~3u) + __uint_as_float(a2.w & ~3u);
            const bool odd = lane & 1;
            float z = (odd ? s2 : s0) + __shfl_xor_sync(0xffffffffu, odd ? s0 : s2, 1);
            float n = (odd ? s3 : s1) + __shfl_xor_sync(0xffffffffu, odd ? s1 : s3, 1);
            const bool hi = lane & 2;
            float v = (hi ? n : z) + __shfl_xor_sync(0xffffffffu, hi ? z : n, 2);
#pragma unroll
            for (int o = 4; o < 32; o <<= 1) v += __shfl_xor_sync(0xffffffffu, v, o);
            n = __shfl_down_sync(0xffffffffu, v, 2) + dn;
            z = v + dz;
            if (lane < 2) {
                out[cta * 8 + (t >> 5) * 2 + lane] = __float2bfloat16(__fdividef(n, z));
                if (!(z > 0.f && z < 3.0e38f && fabsf(n) < 3.0e38f)) sts32(sMisc + 8, 1);
            }
        }
        __syncwarp();
        BAR_ARRIVE(5, 512);
    } else {
        asm volatile("setmaxnreg.inc.sync.aligned.u32 152;");
        const int tid = T - 128;
        const int warp = tid >> 5;
        const int r = lane >> 2, q = lane & 3;
        const int wg = warp >> 2, wq = warp & 3;
        const int u = tI * 192 + warp * 16 + r;
        int4 iv = make_int4(0, 0, 0, 0);
        if (tid < 200) iv = __ldg(reinterpret_cast<const int4*>(idx + (builder ? cta : 0) * 8 * kF) + tid);
        {
            const int ur = tI * 192 + warp * 16 + (lane >> 1);
            const uint32_t dst = sbase + ST_TU + (warp * 16 + (lane >> 1)) * 80 + (lane & 1) * 32;
            const __nv_bfloat16* src = table + min(ur, kV - 1) * kD + (lane & 1) * 16;
            cp16(dst, src, ur < kV);
            cp16(dst + 16, src + 8, ur < kV);
        }
        sts128(sbase + OFF_CB + tid * 16, make_uint4(0, 0, 0, 0));
        if (tid < 120) sts128(sbase + OFF_CB + (384 + tid) * 16, make_uint4(0, 0, 0, 0));
        if (tid == 383) sts32(sMisc + 8, 0);
        asm volatile("barrier.cluster.arrive.relaxed.aligned;" ::: "memory");
        BAR_SYNC(4, 384);
        if (tid < 200) {
            const unsigned vals[4] = {(unsigned)iv.x, (unsigned)iv.y, (unsigned)iv.z, (unsigned)iv.w};
            const int row = tid / 25;
            const uint32_t rb = sbase + OFF_CB + (row >> 1) * 32 + (row & 1) * 4;
            bool badidx = false;
#pragma unroll
            for (int i = 0; i < 4; ++i) {
                badidx |= vals[i] >= (unsigned)kV;
                const unsigned v = min(vals[i], 1007u);
                const uint32_t off = rb + (v >> 4) * 128 + ((v << 2) & 24);
                const uint32_t inc = 1u << (((v << 1) & 16) + ((v & 1) << 3));
                asm volatile("red.shared.add.u32 [%0], %1;" ::"r"(off), "r"(inc) : "memory");
            }
            if (badidx) sts32(sMisc + 8, 1);
        }
        BAR_SYNC(4, 384);
        if (builder) {
            uint4* dst = gC + ((cta >> 5) * kV16 + (tid >> 3)) * 256 + (cta & 31) * 8 + (tid & 7);
            dst[0] = lds128(sbase + OFF_CB + tid * 16);
            if (tid < 120) dst[48 * 256] = lds128(sbase + OFF_CB + (384 + tid) * 16);
        }
        BAR_ARRIVE(1, 416);

        {
            uint32_t ab[8], af[8];
            asm volatile("cp.async.wait_all;" ::: "memory");
            __syncwarp();
            {
                const uint32_t la = sbase + ST_TU + (warp * 16 + (lane & 15)) * 80 + (lane >> 4) * 16;
                asm volatile("ldmatrix.sync.aligned.m8n8.x4.shared.b16 {%0,%1,%2,%3}, [%4];"
                             : "=r"(ab[0]), "=r"(ab[1]), "=r"(ab[2]), "=r"(ab[3]) : "r"(la) : "memory");
                asm volatile("ldmatrix.sync.aligned.m8n8.x4.shared.b16 {%0,%1,%2,%3}, [%4];"
                             : "=r"(ab[4]), "=r"(ab[5]), "=r"(ab[6]), "=r"(ab[7]) : "r"(la + 32) : "memory");
            }
#pragma unroll
            for (int i = 0; i < 8; ++i) af[i] = bf2h(ab[i]);
            bool bad = bf_exceeds<4>(ab[0], ab[1], ab[2], ab[3]) || bf_exceeds<4>(ab[4], ab[5], ab[6], ab[7]);

            float e[12], sv[12];
            uint32_t e2[6];
            uint32_t acc0[24], acc1[24];
            const uint64_t dG = make_desc(sbase + OFF_G, 128, 512);
            const uint32_t cst = sbase + OFF_CST;
            auto issue = [&](uint32_t (&acc)[24], int c) {
                wg_fence();
                mma_h96(acc, af[0], af[1], af[2], af[3], dG + ((c * 6144) >> 4), 0);
                mma_h96(acc, af[4], af[5], af[6], af[7], dG + ((c * 6144 + 256) >> 4), 1);
                wg_commit();
            };
            auto consume = [&](uint32_t (&acc)[24], const uint4& cb, const uint4& ch, bool first) {
                const uint32_t bb[4] = {cb.x, cb.y, cb.z, cb.w}, hh[4] = {ch.x, ch.y, ch.z, ch.w};
#pragma unroll
                for (int ai = 0; ai < 4; ++ai) {
#pragma unroll
                    for (int j = 0; j < 6; ++j)
                        e2[j] = hfma2(hadd2_relu(acc[ai * 6 + j], bb[ai]), hh[ai], (first && ai == 0) ? 0u : e2[j]);
                }
            };
            BAR_SYNC(2, 480);
            {
                const int kb = warp & 3, v8 = lane & 7;
                const uint4 tv = lds128(sbase + ST_TV + (v8 + 8 * wg) * 80 + kb * 16);
                const uint32_t wp = sbase + ST_W + (lane >> 3) * 80 + kb * 16;
                const uint32_t gaddr = sbase + OFF_G + (lane >> 3) * 1536 + wg * 512 + kb * 128 + v8 * 16;
                uint4 wr[8];
#pragma unroll
                for (int i = 0; i < 8; ++i) wr[i] = lds128(wp + i * 320);
#pragma unroll
                for (int i = 0; i < 8; ++i)
                    sts128(gaddr + i * 6144, make_uint4(hmul2(tv.x, wr[i].x), hmul2(tv.y, wr[i].y),
                                                        hmul2(tv.z, wr[i].z), hmul2(tv.w, wr[i].w)));
                asm volatile("fence.proxy.async.shared::cta;" ::: "memory");
                BAR_ARRIVE(13, 512);
                BAR_SYNC(14, 512);
            }
            wg_fence();
            mma_n24(sv, ab[0], ab[1], ab[2], ab[3], dG + (49152 >> 4), 0);
            mma_n24(sv, ab[4], ab[5], ab[6], ab[7], dG + ((49152 + 256) >> 4), 1);
            issue(acc0, 0);
            issue(acc1, 1);
            {
                const float mneg = __uint_as_float(lds32(sMisc + 12));
#pragma unroll
                for (int i = 0; i < 12; ++i) e[i] = mneg;
            }
#pragma unroll
            for (int c = 0; c < 8; c += 2) {
                {
                    const uint4 cb = lds128(cst + c * 32), ch = lds128(cst + c * 32 + 16);
                    wg_wait<1>();
                    consume(acc0, cb, ch, (c & 3) == 0);
                    if (c < 6) issue(acc0, c + 2);
                }
                {
                    const uint4 cb = lds128(cst + c * 32 + 32), ch = lds128(cst + c * 32 + 48);
                    if (c < 6) wg_wait<1>(); else wg_wait<0>();
                    consume(acc1, cb, ch, false);
                    if (c < 6) issue(acc1, c + 3);
                }
                if (c & 2) {
#pragma unroll
                    for (int j = 0; j < 6; ++j) { e[2 * j] += h_lo(e2[j]); e[2 * j + 1] += h_hi(e2[j]); }
                }
            }
            const uint32_t tagbits = (lds32(sMisc) + 1) & 3;
            const bool poison = bad || lds32(sMisc + 4) != 0;
            asm volatile("barrier.cluster.wait.acquire.aligned;" ::: "memory");
            float X[12], Y[12];
            float mx = 0.f, ms = 0.f;
#pragma unroll
            for (int i = 0; i < 12; ++i) {
                mx = maxnan_abs(mx, e[i]);
                ms = maxnan_abs(ms, sv[i]);
                X[i] = ex2(e[i]);
                Y[i] = X[i] * sv[i];
            }
            if (tI == (tj >> 2)) {
                const int dv = u - vb0 - 2 * q;
#pragma unroll
                for (int i = 0; i < 12; ++i) {
                    const int th = 8 * (i >> 2) + (i & 1) - 8 * ((i >> 1) & 1);
                    if (dv == th) {
                        const uint32_t dx = (__float_as_uint(X[i]) & ~3u) | tagbits, dy = (__float_as_uint(Y[i]) & ~3u) | tagbits;
                        asm volatile("st.relaxed.gpu.global.v2.u32 [%0], {%1,%2};"
                                     ::"l"(gDiag + u + 8 * ((i >> 1) & 1)), "r"(dx), "r"(dy) : "memory");
                    }
                    X[i] = (dv < th) ? X[i] : 0.f;
                    Y[i] = (dv < th) ? Y[i] : 0.f;
                }
            }
            uint32_t xh[6], yh[6];
#pragma unroll
            for (int j = 0; j < 6; ++j) {
                xh[j] = pack_bf16(X[2 * j], X[2 * j + 1]);
                yh[j] = pack_bf16(Y[2 * j], Y[2 * j + 1]);
            }
            if (!(mx <= 56.f) || !(ms <= 1.0e15f) || (ms != 0.f && ms < 1.0e-15f) || poison) xh[0] = 0x7FC07FC0u;
            const uint32_t b2 = sbase + OFF_B2 + warp * 3072 + rank * 1536;
            const uint32_t dst = b2 + lane * 16;
            asm volatile("stmatrix.sync.aligned.m8n8.x4.trans.shared.b16 [%0], {%1,%2,%3,%4};"
                         ::"r"(dst), "r"(xh[0]), "r"(xh[1]), "r"(xh[2]), "r"(xh[3]) : "memory");
            asm volatile("stmatrix.sync.aligned.m8n8.x4.trans.shared.b16 [%0], {%1,%2,%3,%4};"
                         ::"r"(dst + 512), "r"(xh[4]), "r"(xh[5]), "r"(yh[0]), "r"(yh[1]) : "memory");
            asm volatile("stmatrix.sync.aligned.m8n8.x4.trans.shared.b16 [%0], {%1,%2,%3,%4};"
                         ::"r"(dst + 1024), "r"(yh[2]), "r"(yh[3]), "r"(yh[4]), "r"(yh[5]) : "memory");
            __syncwarp();
            {
                uint32_t rdst, rbar;
                asm volatile("mapa.shared::cluster.u32 %0, %1, %2;" : "=r"(rdst) : "r"(dst), "r"(rank ^ 1));
                asm volatile("mapa.shared::cluster.u32 %0, %1, %2;" : "=r"(rbar) : "r"(sbase + OFF_BAR + 16), "r"(rank ^ 1));
#pragma unroll
                for (int i = 0; i < 3; ++i) {
                    const uint4 v = lds128(dst + i * 512);
                    asm volatile("st.async.weak.shared::cluster.mbarrier::complete_tx::bytes.v4.b32 [%0], {%1,%2,%3,%4}, [%5];"
                                 ::"r"(rdst + i * 512), "r"(v.x), "r"(v.y), "r"(v.z), "r"(v.w), "r"(rbar) : "memory");
                }
            }
        }

        {
            const uint64_t dB = make_desc(sbase + OFF_B2, 128, 256);
            const uint32_t cb0 = sbase + OFF_C + (tid & 127) * 8;
            uint32_t cb = cb0 + wg * 1024;
            uint32_t* pdst = reinterpret_cast<uint32_t*>(gPart) +
                             (((rank * 8 + wg) * 8 + wq * 2 + (r >> 2)) * kTiles + tile) * 16 + (lane & 15);
            uint32_t aA[24], aB[24];
            float acc[48];
            float z0 = 0.f, n0 = 0.f, z1 = 0.f, n1 = 0.f;
            const uint32_t tagbits = (lds32(sMisc) + 1) & 3;

            auto loadA = [&](uint32_t (&a)[24], uint32_t addr) {
#pragma unroll
                for (int s = 0; s < 6; ++s) {
                    const uint2 raw = lds64(addr + s * 4096);
                    a[4 * s + 0] = cnt2bf<0x4140>(raw.x);
                    a[4 * s + 1] = cnt2bf<0x4140>(raw.y);
                    a[4 * s + 2] = cnt2bf<0x4342>(raw.x);
                    a[4 * s + 3] = cnt2bf<0x4342>(raw.y);
                }
            };
            auto mmas = [&](uint32_t (&a)[24], int h) {
                wg_fence();
#pragma unroll
                for (int s = 0; s < 6; ++s)
                    mma_n96(acc, a[4 * s], a[4 * s + 1], a[4 * s + 2], a[4 * s + 3], dB + (((h * 6 + s) * 3072) >> 4),
                            !(h == 0 && s == 0));
                wg_commit();
            };
            auto flush = [&](uint32_t* p) {
                const bool odd = q & 1;
                float s0 = odd ? z0 : n0, k0 = odd ? n0 : z0;
                float s1 = odd ? z1 : n1, k1 = odd ? n1 : z1;
                k0 += __shfl_xor_sync(0xffffffffu, s0, 1);
                k1 += __shfl_xor_sync(0xffffffffu, s1, 1);
                const bool hi = q & 2;
                float s2 = hi ? k0 : k1, k2 = hi ? k1 : k0;
                k2 += __shfl_xor_sync(0xffffffffu, s2, 2);
                const uint32_t val = (__float_as_uint(k2) & ~3u) | tagbits;
                asm volatile("st.relaxed.gpu.global.u32 [%0], %1;" ::"l"(p), "r"(val) : "memory");
            };

            BAR_ARRIVE(15, 512);
            mbar_wait(sbase + OFF_BAR, 0);
            loadA(aA, cb);
            loadA(aB, cb + 24576);
            asm volatile("fence.proxy.async.shared::cta;" ::: "memory");
            BAR_SYNC(4, 384);
            mbar_wait_cluster(sbase + OFF_BAR + 16, 0);
            asm volatile("fence.proxy.async.shared::cta;" ::: "memory");
            const int nblk = wg < 2 ? 3 : 2;
#pragma unroll 1
            for (int it = 0; it < nblk; ++it) {
                mmas(aA, 0);
                if (it > 0) {
                    flush(pdst - 3 * 8 * kTiles * 16);
                    loadA(aB, cb + 24576);
                }
                mmas(aB, 1);
                float c0[12], c1[12];
#pragma unroll
                for (int t = 0; t < 3; ++t) {
                    const uint2 raw = lds64(cb + 49152 + t * 4096);
                    c0[4 * t + 0] = cnt2f<0x7440>(raw.x); c0[4 * t + 1] = cnt2f<0x7441>(raw.x);
                    c0[4 * t + 2] = cnt2f<0x7442>(raw.x); c0[4 * t + 3] = cnt2f<0x7443>(raw.x);
                    c1[4 * t + 0] = cnt2f<0x7440>(raw.y); c1[4 * t + 1] = cnt2f<0x7441>(raw.y);
                    c1[4 * t + 2] = cnt2f<0x7442>(raw.y); c1[4 * t + 3] = cnt2f<0x7443>(raw.y);
                }
                wg_wait<1>();
                const int nxt = wg + 3 * it + 3;
                const uint32_t cbn = cb0 + (nxt >> 2) * kQuart + (nxt & 3) * 1024;
                if (it + 1 < nblk) {
                    mbar_wait(sbase + OFF_BAR + (nxt >> 2) * 8, 0);
                    loadA(aA, cbn);
                }
                wg_wait<0>();
                float za = 0.f, zb = 0.f, zc = 0.f, zd = 0.f, na = 0.f, nb = 0.f, nc = 0.f, nd = 0.f;
#pragma unroll
                for (int vb = 0; vb < 6; ++vb) {
                    const int xb = ((vb / 3) * 6 + vb % 3) * 4, yb = xb + 12;
                    za = fmaf(acc[xb + 0], c0[2 * vb], za);
                    zb = fmaf(acc[xb + 1], c0[2 * vb + 1], zb);
                    zc = fmaf(acc[xb + 2], c1[2 * vb], zc);
                    zd = fmaf(acc[xb + 3], c1[2 * vb + 1], zd);
                    na = fmaf(acc[yb + 0], c0[2 * vb], na);
                    nb = fmaf(acc[yb + 1], c0[2 * vb + 1], nb);
                    nc = fmaf(acc[yb + 2], c1[2 * vb], nc);
                    nd = fmaf(acc[yb + 3], c1[2 * vb + 1], nd);
                }
                z0 = za + zb; z1 = zc + zd; n0 = na + nb; n1 = nc + nd;
                cb = cbn;
                pdst += 3 * 8 * kTiles * 16;
            }
            flush(pdst - 3 * 8 * kTiles * 16);
            if (wg == 2) BAR_ARRIVE(12, 256);
        }
        BAR_SYNC(5, 512);
        if (builder && lds32(sMisc + 8) != 0) fallback_rows(idx, table, ii, jj, W, bv, hv, pv, out, smem, cta * 8, tid);
    }
}

}

extern "C" void kernel_launch(void* const* d_in, const int* in_sizes, int n_in, void* d_out, int out_size) {
    (void)in_sizes; (void)n_in; (void)out_size;
    static bool init_done = false;
    static bool fits = false;
    static void *pC = nullptr, *pPart = nullptr, *pCnt = nullptr, *pDiag = nullptr;
    if (!init_done) {
        cudaFuncSetAttribute(afm_kernel, cudaFuncAttributeMaxDynamicSharedMemorySize, SMEM_BYTES);
        cudaGetSymbolAddress(&pC, g_C);
        cudaGetSymbolAddress(&pPart, g_part);
        cudaGetSymbolAddress(&pCnt, g_cnt);
        cudaGetSymbolAddress(&pDiag, g_diag);
        cudaLaunchConfig_t cfg = {};
        cfg.gridDim = dim3(kGrid);
        cfg.blockDim = dim3(kThreads);
        cfg.dynamicSmemBytes = SMEM_BYTES;
        cudaLaunchAttribute at;
        at.id = cudaLaunchAttributeClusterDimension;
        at.val.clusterDim.x = 2; at.val.clusterDim.y = 1; at.val.clusterDim.z = 1;
        cfg.attrs = &at;
        cfg.numAttrs = 1;
        int ncl = 0;
        fits = cudaOccupancyMaxActiveClusters(&ncl, afm_kernel, &cfg) == cudaSuccess && ncl >= kTiles;
        (void)cudaGetLastError();
        init_done = true;
    }
    const int* idx = (const int*)d_in[0];
    const __nv_bfloat16* table = (const __nv_bfloat16*)d_in[1];
    const int* ii = (const int*)d_in[2];
    const int* jj = (const int*)d_in[3];
    const __nv_bfloat16* W = (const __nv_bfloat16*)d_in[4];
    const __nv_bfloat16* b = (const __nv_bfloat16*)d_in[5];
    const __nv_bfloat16* h = (const __nv_bfloat16*)d_in[6];
    const __nv_bfloat16* p = (const __nv_bfloat16*)d_in[7];
    if (fits) {
        afm_kernel<<<kGrid, kThreads, SMEM_BYTES>>>(idx, table, ii, jj, W, b, h, p, (__nv_bfloat16*)d_out,
                                                    (uint4*)pC, (uint4*)pPart, (uint2*)pDiag, (unsigned*)pCnt);
    } else {
        afm_direct_kernel<<<128, 384>>>(idx, table, ii, jj, W, b, h, p, (__nv_bfloat16*)d_out);
    }
}
```

```cpp
#include <cuda_runtime.h>
#include <cuda_bf16.h>
#include <stdint.h>

namespace {

constexpr int kF = 100, kD = 32, kV = 1000, kP = 4950;
constexpr int kV16 = 63;
constexpr int kTiles = 66;
constexpr int kGrid = 132;
constexpr int kThreads = 512;
constexpr int kQuart = 61440;

constexpr int OFF_C = 0;
constexpr int OFF_B2 = OFF_C + 2 * kQuart;
constexpr int OFF_G = OFF_B2 + 36864;
constexpr int OFF_CB = OFF_G + 50688;
constexpr int OFF_CST = OFF_CB + 8064;
constexpr int OFF_BAR = OFF_CST + 256;
constexpr int OFF_MISC = OFF_BAR + 64;
constexpr int SMEM_BYTES = OFF_MISC + 64;
constexpr int ST_TU = OFF_C;
constexpr int ST_TV = ST_TU + 15360;
constexpr int ST_W = ST_TV + 1920;

__device__ uint4 g_C[16 * kV16 * 64];
__device__ uint4 g_part[128 * kTiles * 4];
__device__ uint2 g_diag[1024];
__device__ unsigned g_cnt[5 * 32];


__device__ __forceinline__ uint32_t smem_u32(const void* p) {
    return (uint32_t)__cvta_generic_to_shared(p);
}
__device__ __forceinline__ uint64_t make_desc(uint32_t addr, uint32_t lbo, uint32_t sbo) {
    return (uint64_t)((addr & 0x3FFFF) >> 4) | ((uint64_t)(lbo >> 4) << 16) | ((uint64_t)(sbo >> 4) << 32);
}
__device__ __forceinline__ void wg_fence() { asm volatile("wgmma.fence.sync.aligned;" ::: "memory"); }
__device__ __forceinline__ void wg_commit() { asm volatile("wgmma.commit_group.sync.aligned;" ::: "memory"); }
template <int N>
__device__ __forceinline__ void wg_wait() { asm volatile("wgmma.wait_group.sync.aligned %0;" ::"n"(N) : "memory"); }

__device__ __forceinline__ void mma_n24(float (&d)[12], uint32_t a0, uint32_t a1, uint32_t a2, uint32_t a3,
                                        uint64_t desc, int scale_d) {
    asm volatile(
        "{\n.reg .pred p;\nsetp.ne.b32 p, %17, 0;\n"
        "wgmma.mma_async.sync.aligned.m64n24k16.f32.bf16.bf16 "
        "{%0,%1,%2,%3,%4,%5,%6,%7,%8,%9,%10,%11},"
        "{%12,%13,%14,%15}, %16, p, 1, 1, 0;\n}\n"
        : "+f"(d[0]), "+f"(d[1]), "+f"(d[2]), "+f"(d[3]), "+f"(d[4]), "+f"(d[5]), "+f"(d[6]), "+f"(d[7]),
          "+f"(d[8]), "+f"(d[9]), "+f"(d[10]), "+f"(d[11])
        : "r"(a0), "r"(a1), "r"(a2), "r"(a3), "l"(desc), "r"(scale_d));
}

__device__ __forceinline__ void mma_h96(uint32_t (&d)[24], uint32_t a0, uint32_t a1, uint32_t a2, uint32_t a3,
                                        uint64_t desc, int scale_d) {
    asm volatile(
        "{\n.reg .pred p;\nsetp.ne.b32 p, %29, 0;\n"
        "wgmma.mma_async.sync.aligned.m64n96k16.f16.f16.f16 "
        "{%0,%1,%2,%3,%4,%5,%6,%7,%8,%9,%10,%11,%12,%13,%14,%15,%16,%17,%18,%19,%20,%21,%22,%23},"
        "{%24,%25,%26,%27}, %28, p, 1, 1, 0;\n}\n"
        : "+r"(d[0]), "+r"(d[1]), "+r"(d[2]), "+r"(d[3]), "+r"(d[4]), "+r"(d[5]), "+r"(d[6]), "+r"(d[7]),
          "+r"(d[8]), "+r"(d[9]), "+r"(d[10]), "+r"(d[11]), "+r"(d[12]), "+r"(d[13]), "+r"(d[14]), "+r"(d[15]),
          "+r"(d[16]), "+r"(d[17]), "+r"(d[18]), "+r"(d[19]), "+r"(d[20]), "+r"(d[21]), "+r"(d[22]), "+r"(d[23])
        : "r"(a0), "r"(a1), "r"(a2), "r"(a3), "l"(desc), "r"(scale_d));
}

__device__ __forceinline__ void mma_n96(float (&d)[48], uint32_t a0, uint32_t a1, uint32_t a2, uint32_t a3,
                                        uint64_t desc, int scale_d) {
    asm volatile(
        "{\n.reg .pred p;\nsetp.ne.b32 p, %53, 0;\n"
        "wgmma.mma_async.sync.aligned.m64n96k16.f32.bf16.bf16 "
        "{%0,%1,%2,%3,%4,%5,%6,%7,%8,%9,%10,%11,%12,%13,%14,%15,%16,%17,%18,%19,%20,%21,%22,%23,"
        "%24,%25,%26,%27,%28,%29,%30,%31,%32,%33,%34,%35,%36,%37,%38,%39,%40,%41,%42,%43,%44,%45,%46,%47},"
        "{%48,%49,%50,%51}, %52, p, 1, 1, 0;\n}\n"
        : "+f"(d[0]), "+f"(d[1]), "+f"(d[2]), "+f"(d[3]), "+f"(d[4]), "+f"(d[5]), "+f"(d[6]), "+f"(d[7]),
          "+f"(d[8]), "+f"(d[9]), "+f"(d[10]), "+f"(d[11]), "+f"(d[12]), "+f"(d[13]), "+f"(d[14]), "+f"(d[15]),
          "+f"(d[16]), "+f"(d[17]), "+f"(d[18]), "+f"(d[19]), "+f"(d[20]), "+f"(d[21]), "+f"(d[22]), "+f"(d[23]),
          "+f"(d[24]), "+f"(d[25]), "+f"(d[26]), "+f"(d[27]), "+f"(d[28]), "+f"(d[29]), "+f"(d[30]), "+f"(d[31]),
          "+f"(d[32]), "+f"(d[33]), "+f"(d[34]), "+f"(d[35]), "+f"(d[36]), "+f"(d[37]), "+f"(d[38]), "+f"(d[39]),
          "+f"(d[40]), "+f"(d[41]), "+f"(d[42]), "+f"(d[43]), "+f"(d[44]), "+f"(d[45]), "+f"(d[46]), "+f"(d[47])
        : "r"(a0), "r"(a1), "r"(a2), "r"(a3), "l"(desc), "r"(scale_d));
}

__device__ __forceinline__ uint32_t bmul2(uint32_t a, uint32_t b) {
    uint32_t r;
    asm("mul.rn.bf16x2 %0, %1, %2;" : "=r"(r) : "r"(a), "r"(b));
    return r;
}
__device__ __forceinline__ uint32_t pack_bf16(float lo, float hi) {
    uint32_t r;
    asm("cvt.rn.bf16x2.f32 %0, %1, %2;" : "=r"(r) : "f"(hi), "f"(lo));
    return r;
}
__device__ __forceinline__ float bf_lo(uint32_t x) { return __uint_as_float(x << 16); }
__device__ __forceinline__ float bf_hi(uint32_t x) { return __uint_as_float(x & 0xffff0000u); }
__device__ __forceinline__ uint32_t pack_f16(float lo, float hi) {
    uint32_t r;
    asm("cvt.rn.f16x2.f32 %0, %1, %2;" : "=r"(r) : "f"(hi), "f"(lo));
    return r;
}
__device__ __forceinline__ uint32_t bf2h(uint32_t x) { return pack_f16(bf_lo(x), bf_hi(x)); }
__device__ __forceinline__ uint32_t hmul2(uint32_t a, uint32_t b) {
    uint32_t r;
    asm("mul.rn.f16x2 %0, %1, %2;" : "=r"(r) : "r"(a), "r"(b));
    return r;
}
__device__ __forceinline__ uint32_t hfma2(uint32_t a, uint32_t b, uint32_t c) {
    uint32_t r;
    asm("fma.rn.f16x2 %0, %1, %2, %3;" : "=r"(r) : "r"(a), "r"(b), "r"(c));
    return r;
}
__device__ __forceinline__ uint32_t hadd2_relu(uint32_t a, uint32_t c) {
    uint32_t r;
    asm("fma.rn.relu.f16x2 %0, %1, %2, %3;" : "=r"(r) : "r"(a), "r"(0x3C003C00u), "r"(c));
    return r;
}
__device__ __forceinline__ float h_lo(uint32_t x) {
    float r;
    asm("{.reg .f16 l, h; mov.b32 {l, h}, %1; cvt.f32.f16 %0, l;}" : "=f"(r) : "r"(x));
    return r;
}
__device__ __forceinline__ float h_hi(uint32_t x) {
    float r;
    asm("{.reg .f16 l, h; mov.b32 {l, h}, %1; cvt.f32.f16 %0, h;}" : "=f"(r) : "r"(x));
    return r;
}
template <int LOG2>
__device__ __forceinline__ bool bf_exceeds(uint32_t a, uint32_t b, uint32_t c, uint32_t d) {
    const uint32_t m = 0x7fff7fffu;
    const uint32_t mx = __vmaxu2(__vmaxu2(a & m, b & m), __vmaxu2(c & m, d & m));
    return __vcmpgtu2(mx, ((127u + LOG2) << 7) * 0x10001u) != 0;
}
__device__ __forceinline__ float ex2(float x) {
    float r;
    asm("ex2.approx.ftz.f32 %0, %1;" : "=f"(r) : "f"(x));
    return r;
}
__device__ __forceinline__ float maxnan_abs(float m, float x) {
    float r;
    asm("max.NaN.f32 %0, %1, %2;" : "=f"(r) : "f"(m), "f"(fabsf(x)));
    return r;
}
__device__ __forceinline__ uint4 lds128(uint32_t a) {
    uint4 v;
    asm volatile("ld.shared.v4.u32 {%0,%1,%2,%3}, [%4];" : "=r"(v.x), "=r"(v.y), "=r"(v.z), "=r"(v.w) : "r"(a));
    return v;
}
__device__ __forceinline__ uint2 lds64(uint32_t a) {
    uint2 v;
    asm volatile("ld.shared.v2.u32 {%0,%1}, [%2];" : "=r"(v.x), "=r"(v.y) : "r"(a));
    return v;
}
__device__ __forceinline__ uint32_t lds32(uint32_t a) {
    uint32_t v;
    asm volatile("ld.shared.u32 %0, [%1];" : "=r"(v) : "r"(a) : "memory");
    return v;
}
__device__ __forceinline__ uint32_t lds32_nv(uint32_t a) {
    uint32_t v;
    asm("ld.shared.u32 %0, [%1];" : "=r"(v) : "r"(a));
    return v;
}
__device__ __forceinline__ uint32_t opaque(uint32_t a) {
    asm volatile("" : "+r"(a) :: "memory");
    return a;
}
__device__ __forceinline__ void sts128(uint32_t a, uint4 v) {
    asm volatile("st.shared.v4.u32 [%0], {%1,%2,%3,%4};" ::"r"(a), "r"(v.x), "r"(v.y), "r"(v.z), "r"(v.w) : "memory");
}
__device__ __forceinline__ void sts16(uint32_t a, uint32_t x) {
    asm volatile("st.shared.u16 [%0], %1;" ::"r"(a), "h"((unsigned short)x) : "memory");
}
__device__ __forceinline__ void sts32(uint32_t a, uint32_t x) {
    asm volatile("st.shared.u32 [%0], %1;" ::"r"(a), "r"(x) : "memory");
}
__device__ __forceinline__ void mbar_wait(uint32_t bar, uint32_t parity) {
    uint32_t done = 0;
    for (int it = 0; it < (1 << 16) && !done; ++it) {
        asm volatile(
            "{\n.reg .pred p;\nmbarrier.try_wait.parity.shared::cta.b64 p, [%1], %2;\nselp.u32 %0, 1, 0, p;\n}\n"
            : "=r"(done) : "r"(bar), "r"(parity) : "memory");
    }
}
__device__ __forceinline__ void mbar_wait_cluster(uint32_t bar, uint32_t parity) {
    uint32_t done = 0;
    for (int it = 0; it < (1 << 16) && !done; ++it) {
        asm volatile(
            "{\n.reg .pred p;\nmbarrier.try_wait.parity.acquire.cluster.shared::cta.b64 p, [%1], %2;\nselp.u32 %0, 1, 0, p;\n}\n"
            : "=r"(done) : "r"(bar), "r"(parity) : "memory");
    }
}
__device__ __forceinline__ void cp16(uint32_t dst, const void* src, bool valid) {
    asm volatile("cp.async.cg.shared.global [%0], [%1], 16, %2;" ::"r"(dst), "l"(src), "r"(valid ? 16 : 0) : "memory");
}
#define BAR_SYNC(id, n) asm volatile("bar.sync " #id ", " #n ";" ::: "memory")
#define BAR_ARRIVE(id, n) asm volatile("bar.arrive " #id ", " #n ";" ::: "memory")
template <int SEL>
__device__ __forceinline__ uint32_t cnt2bf(uint32_t w) {
    uint32_t r;
    asm volatile("{\n.reg .b32 t;\nprmt.b32 t, %1, 0x43434343, %2;\nadd.rn.bf16x2 %0, t, %3;\n}\n"
                 : "=r"(r) : "r"(w), "n"(SEL), "r"(0xC300C300u));
    return r;
}
template <int SEL>
__device__ __forceinline__ float cnt2f(uint32_t w) {
    float r;
    asm volatile("{\n.reg .b32 t;\nprmt.b32 t, %1, 0x4B000000, %2;\nadd.rn.f32 %0, t, 0fCB000000;\n}\n"
                 : "=f"(r) : "r"(w), "n"(SEL));
    return r;
}

__device__ __noinline__ void fallback_rows(const int* __restrict__ idx, const __nv_bfloat16* __restrict__ table,
                                           const int* __restrict__ ii, const int* __restrict__ jj,
                                           const __nv_bfloat16* __restrict__ W, const __nv_bfloat16* __restrict__ bv,
                                           const __nv_bfloat16* __restrict__ hv, const __nv_bfloat16* __restrict__ pv,
                                           __nv_bfloat16* __restrict__ out, unsigned char* smem, int b0, int tid) {
    float* sW = reinterpret_cast<float*>(smem);
    float* sb = sW + 1024;
    float* sh = sb + 32;
    float* sp = sh + 32;
    float* sE = sp + 32;
    float* sR = sE + kF * 33;
    for (int i = tid; i < 1024; i += 384) sW[i] = __bfloat162float(W[i]);
    if (tid < 32) {
        sb[tid] = __bfloat162float(bv[tid]);
        sh[tid] = __bfloat162float(hv[tid]);
        sp[tid] = __bfloat162float(pv[tid]);
    }
    for (int r = 0; r < 8; ++r) {
        const int b = b0 + r;
        BAR_SYNC(6, 384);
        for (int i = tid; i < kF * kD; i += 384) {
            int f = i >> 5, d = i & 31;
            int v = idx[b * kF + f];
            if (v < 0) v += kV;
            v = min(max(v, 0), kV - 1);
            sE[f * 33 + d] = __bfloat162float(table[v * kD + d]);
        }
        BAR_SYNC(6, 384);
        float m = -INFINITY, z = 0.f, n = 0.f;
        for (int k = tid; k < kP; k += 384) {
            int i = ii[k], j = jj[k];
            if (i < 0) i += kF;
            if (j < 0) j += kF;
            i = min(max(i, 0), kF - 1);
            j = min(max(j, 0), kF - 1);
            float hid[32];
#pragma unroll
            for (int a = 0; a < 32; ++a) hid[a] = sb[a];
            float s = 0.f;
            for (int d = 0; d < 32; ++d) {
                float pr = __bfloat162float(__float2bfloat16(sE[i * 33 + d] * sE[j * 33 + d]));
                s = fmaf(pr, sp[d], s);
#pragma unroll
                for (int a = 0; a < 32; a += 4) {
                    float4 w = *reinterpret_cast<const float4*>(sW + d * 32 + a);
                    hid[a] = fmaf(pr, w.x, hid[a]);
                    hid[a + 1] = fmaf(pr, w.y, hid[a + 1]);
                    hid[a + 2] = fmaf(pr, w.z, hid[a + 2]);
                    hid[a + 3] = fmaf(pr, w.w, hid[a + 3]);
                }
            }
            float e = 0.f;
#pragma unroll
            for (int a = 0; a < 32; ++a) e = fmaf(0.5f * (hid[a] + fabsf(hid[a])), sh[a], e);
            float mn = fmaxf(m, e);
            float c = __expf(m - mn), w = __expf(e - mn);
            if (m == -INFINITY) c = 0.f;
            z = z * c + w;
            n = n * c + w * s;
            m = mn;
        }
#pragma unroll
        for (int o = 16; o > 0; o >>= 1) {
            float m2 = __shfl_xor_sync(0xffffffffu, m, o);
            float z2 = __shfl_xor_sync(0xffffffffu, z, o);
            float n2 = __shfl_xor_sync(0xffffffffu, n, o);
            float mn = fmaxf(m, m2);
            float c1 = (m == -INFINITY) ? 0.f : __expf(m - mn);
            float c2 = (m2 == -INFINITY) ? 0.f : __expf(m2 - mn);
            z = z * c1 + z2 * c2;
            n = n * c1 + n2 * c2;
            m = mn;
        }
        if ((tid & 31) == 0) {
            sR[(tid >> 5) * 3 + 0] = m;
            sR[(tid >> 5) * 3 + 1] = z;
            sR[(tid >> 5) * 3 + 2] = n;
        }
        BAR_SYNC(6, 384);
        if (tid == 0) {
            float mm = -INFINITY;
            for (int w = 0; w < 12; ++w) mm = fmaxf(mm, sR[w * 3]);
            float zz = 0.f, nn = 0.f;
            for (int w = 0; w < 12; ++w) {
                float c = (sR[w * 3] == -INFINITY) ? 0.f : __expf(sR[w * 3] - mm);
                zz += sR[w * 3 + 1] * c;
                nn += sR[w * 3 + 2] * c;
            }
            out[b] = __float2bfloat16(nn / zz);
        }
    }
}

__global__ void __launch_bounds__(384, 1)
afm_direct_kernel(const int* __restrict__ idx, const __nv_bfloat16* __restrict__ table,
                  const int* __restrict__ ii, const int* __restrict__ jj,
                  const __nv_bfloat16* __restrict__ W, const __nv_bfloat16* __restrict__ bv,
                  const __nv_bfloat16* __restrict__ hv, const __nv_bfloat16* __restrict__ pv,
                  __nv_bfloat16* __restrict__ out) {
    __shared__ __align__(16) unsigned char sm[18432];
    fallback_rows(idx, table, ii, jj, W, bv, hv, pv, out, sm, blockIdx.x * 8, threadIdx.x);
}

__global__ void __cluster_dims__(2, 1, 1) __launch_bounds__(kThreads, 1)
afm_kernel(const int* __restrict__ idx, const __nv_bfloat16* __restrict__ table,
           const int* __restrict__ ii, const int* __restrict__ jj,
           const __nv_bfloat16* __restrict__ W, const __nv_bfloat16* __restrict__ bv,
           const __nv_bfloat16* __restrict__ hv, const __nv_bfloat16* __restrict__ pv,
           __nv_bfloat16* __restrict__ out, uint4* __restrict__ gC, uint4* __restrict__ gPart,
           uint2* __restrict__ gDiag, unsigned* __restrict__ gCnt) {
    extern __shared__ __align__(1024) unsigned char smem[];
    const uint32_t sbase = smem_u32(smem);
    const int T = threadIdx.x;
    const int lane = T & 31;
    const int cta = blockIdx.x;
    const int tile = cta >> 1, rank = cta & 1;
    const bool builder = cta < 128;

    const int tm = (tile >= 4) + (tile >= 12) + (tile >= 24) + (tile >= 40) + (tile >= 60);
    const int trem = tile - 2 * tm * (tm + 1);
    const int trr = (trem >= tm + 1) + (trem >= 2 * (tm + 1)) + (trem >= 3 * (tm + 1));
    const int tI = trem - trr * (tm + 1), tj = 4 * tm + trr;
    const int vb0 = tj * 48 + rank * 24;
    const float kLog2e = 1.44269504088896340736f;
    const uint32_t sMisc = sbase + OFF_MISC;

    if (T < 128) {
        asm volatile("setmaxnreg.dec.sync.aligned.u32 56;");
        const int t = T;
        unsigned* myCnt = gCnt + (cta >> 5) * 32;
        const int j = t - 32;
        uint4 y4 = make_uint4(0, 0, 0, 0), y5 = y4, z4 = y4, p4 = y4;
        if (t >= 32) {
            y4 = __ldg(reinterpret_cast<const uint4*>(W) + j);
            if (j < 32) y5 = __ldg(reinterpret_cast<const uint4*>(W) + 96 + j);
            if (vb0 + (j >> 2) < kV) z4 = __ldg(reinterpret_cast<const uint4*>(table + (vb0 + (j >> 2)) * kD) + (j & 3));
            p4 = __ldg(reinterpret_cast<const uint4*>(pv) + (j & 3));
        }
        uint32_t x0 = 0, x1 = 0, x2 = 0, x3 = 0;
        if (t >= 64) {
            const int kc = min(cta * 38 + (t - 64), kP - 1), kp = max(kc - 1, 0);
            x0 = __ldg(ii + kc); x1 = __ldg(jj + kc); x2 = __ldg(ii + kp); x3 = __ldg(jj + kp);
        } else if (t >= 32) {
            x0 = __ldg(reinterpret_cast<const unsigned short*>(bv) + lane);
            x1 = __ldg(reinterpret_cast<const unsigned short*>(hv) + lane);
        }
        if (t == 0) {
            asm volatile("ld.relaxed.gpu.global.u32 %0, [%1];" : "=r"(x0) : "l"(myCnt) : "memory");
#pragma unroll
            for (int i = 0; i < 3; ++i)
                asm volatile("mbarrier.init.shared::cta.b64 [%0], 1;" ::"r"(sbase + OFF_BAR + i * 8) : "memory");
            const uint32_t qbytes = min(12, kV16 - tI * 12) * 4096 + 12288;
            asm volatile("mbarrier.arrive.expect_tx.shared::cta.b64 _, [%0], %1;" ::"r"(sbase + OFF_BAR), "r"(qbytes) : "memory");
            asm volatile("mbarrier.arrive.expect_tx.shared::cta.b64 _, [%0], %1;" ::"r"(sbase + OFF_BAR + 8), "r"(qbytes) : "memory");
            asm volatile("mbarrier.arrive.expect_tx.shared::cta.b64 _, [%0], %1;" ::"r"(sbase + OFF_BAR + 16), "r"(18432) : "memory");
            asm volatile("fence.mbarrier_init.release.cluster;" ::: "memory");
        }
        __syncwarp();
        asm volatile("barrier.cluster.arrive.relaxed.aligned;" ::: "memory");
        if (t < 32) {
            if (t == 0) sts32(sMisc, builder ? (x0 >> 5) : (x0 >> 2));
            __syncwarp();
            BAR_ARRIVE(14, 512);
            BAR_SYNC(1, 416);
            if (t == 0) asm volatile("red.release.gpu.global.add.u32 [%0], 1;" ::"l"(myCnt) : "memory");
        } else {
            auto put_wt = [&](const uint4& y, int c) {
                const uint32_t wt = sbase + ST_W + (c & 3) * 640 + (c >> 2) * 2;
                const uint32_t w0 = bf2h(y.x), w1 = bf2h(y.y), w2 = bf2h(y.z), w3 = bf2h(y.w);
                sts16(wt, w0); sts16(wt + 80, w0 >> 16); sts16(wt + 160, w1); sts16(wt + 240, w1 >> 16);
                sts16(wt + 320, w2); sts16(wt + 400, w2 >> 16); sts16(wt + 480, w3); sts16(wt + 560, w3 >> 16);
            };
            sts128(sbase + ST_TV + (j >> 2) * 80 + (j & 3) * 16, make_uint4(bf2h(z4.x), bf2h(z4.y), bf2h(z4.z), bf2h(z4.w)));
            put_wt(y4, j);
            if (j < 32) put_wt(y5, 96 + j);
            BAR_ARRIVE(2, 480);
            {
                p4.x = opaque(p4.x); p4.y = opaque(p4.y); p4.z = opaque(p4.z); p4.w = opaque(p4.w);
                const int kb = j & 3, vl = j >> 2;
                sts128(sbase + OFF_G + 49152 + (vl >> 3) * 512 + kb * 128 + (vl & 7) * 16,
                       make_uint4(bmul2(z4.x, p4.x), bmul2(z4.y, p4.y), bmul2(z4.z, p4.z), bmul2(z4.w, p4.w)));
            }
            bool bad = bf_exceeds<3>(y4.x, y4.y, y4.z, y4.w) || bf_exceeds<3>(y5.x, y5.y, y5.z, y5.w) ||
                       bf_exceeds<4>(z4.x, z4.y, z4.z, z4.w);
            if (t < 64) {
                const float bb = __uint_as_float(x0 << 16), hh = __uint_as_float(x1 << 16) * kLog2e;
                sts32(sbase + OFF_CST + (lane >> 2) * 32 + (lane & 3) * 4, pack_f16(bb, bb));
                sts32(sbase + OFF_CST + (lane >> 2) * 32 + 16 + (lane & 3) * 4, pack_f16(hh, hh));
                bad |= !(fabsf(hh) <= 8.f);
                float mm = hh * fmaxf(bb, 0.f);
#pragma unroll
                for (int o = 16; o > 0; o >>= 1) mm += __shfl_xor_sync(0xffffffffu, mm, o);
                if (lane == 0) sts32(sMisc + 12, __float_as_uint(-mm));
            } else {
                const int kk = cta * 38 + (t - 64);
                if (t < 64 + 38 && kk < kP) {
                    const int ci = x0, cj = x1, pi = x2, pj = x3;
                    int ei, ej;
                    if (kk == 0) { ei = 0; ej = 1; }
                    else if (pj + 1 < kF) { ei = pi; ej = pj + 1; }
                    else { ei = pi + 1; ej = pi + 2; }
                    bad |= (ci != ei || cj != ej);
                }
            }
            const uint32_t anybad = __ballot_sync(0xffffffffu, bad);
            if (lane == 0) sts32(sMisc + 16 + (t >> 5) * 4, anybad);
            asm volatile("fence.proxy.async.shared::cta;" ::: "memory");
            BAR_ARRIVE(14, 512);
        }
        BAR_SYNC(13, 512);
        const unsigned epoch = lds32(sMisc);
        const uint32_t tag = (epoch + 1) & 3;
        if (t < 64) {
            const int w = t >> 5;
            const unsigned target = (epoch + 1) << 5;
            const unsigned* cp = gCnt + (rank * 2 + w) * 32;
            const uint32_t abytes = min(12, kV16 - tI * 12) * 4096;
            const unsigned char* gb = reinterpret_cast<const unsigned char*>(gC) + (rank * 2 + w) * (kV16 * 4096);
            const uint32_t bar = sbase + OFF_BAR + w * 8;
            const uint32_t dst = sbase + OFF_C + w * kQuart;
            if (lane == 0) {
                unsigned c;
                for (int it = 0; it < (1 << 18); ++it) {
                    asm volatile("ld.acquire.gpu.global.u32 %0, [%1];" : "=r"(c) : "l"(cp) : "memory");
                    if ((int)(c - target) >= 0) break;
                }
                asm volatile("fence.proxy.async.global;" ::: "memory");
                asm volatile("cp.async.bulk.shared::cluster.global.mbarrier::complete_tx::bytes [%0], [%1], %2, [%3];"
                             ::"r"(dst), "l"(gb + tI * 49152), "r"(abytes), "r"(bar) : "memory");
                asm volatile("cp.async.bulk.shared::cluster.global.mbarrier::complete_tx::bytes [%0], [%1], %2, [%3];"
                             ::"r"(dst + 49152), "l"(gb + tj * 12288), "r"(12288), "r"(bar) : "memory");
            }
            __syncwarp();
        }
        float dz, dn;
        {
            uint32_t dv[8] = {0, 0, 0, 0, 0, 0, 0, 0};
            if (builder) {
                const int row = t >> 4;
                const int* ip = idx + (cta * 8 + row) * kF + (t & 15);
                unsigned vals[7];
#pragma unroll
                for (int i = 0; i < 7; ++i) vals[i] = __ldg(ip + min(16 * i, 99 - (t & 15)));
                const uint32_t rb = opaque(sbase + OFF_CB + (row >> 1) * 32 + (row & 1) * 4);
#pragma unroll
                for (int i = 0; i < 7; ++i) {
                    const unsigned v = min(vals[i], 1007u);
                    uint32_t c = (lds32_nv(rb + (v >> 4) * 128 + ((v << 2) & 24)) >>
                                  (((v << 1) & 16) + ((v & 1) << 3))) & 0xff;
                    if (i == 6 && (t & 15) >= 4) c = 1;
                    dv[i] = v | (c << 16);
                }
            }
            BAR_SYNC(15, 512);
            for (int spin = 0; spin < (1 << 18); ++spin) {
                uint32_t dx[7], dy[7];
#pragma unroll
                for (int i = 0; i < 7; ++i) {
                    dx[i] = tag; dy[i] = tag;
                    asm volatile("{\n.reg .pred p;\nsetp.ge.u32 p, %3, 0x20000;\n"
                                 "@p ld.relaxed.gpu.global.v2.u32 {%0,%1}, [%2];\n}\n"
                                 : "+r"(dx[i]), "+r"(dy[i]) : "l"(gDiag + (dv[i] & 1023)), "r"(dv[i]) : "memory");
                }
                uint32_t bad = 0;
                dz = 0.f; dn = 0.f;
#pragma unroll
                for (int i = 0; i < 7; ++i) {
                    bad |= (dx[i] ^ tag) | (dy[i] ^ tag);
                    const float cc = 0.5f * (float)((int)(dv[i] >> 16) - 1);
                    dz = fmaf(cc, __uint_as_float(dx[i] & ~3u), dz);
                    dn = fmaf(cc, __uint_as_float(dy[i] & ~3u), dn);
                }
                if (!__any_sync(0xffffffffu, (bad & 3u) != 0)) break;
                __nanosleep(200);
            }
#pragma unroll
            for (int o = 1; o < 16; o <<= 1) {
                dz += __shfl_xor_sync(0xffffffffu, dz, o);
                dn += __shfl_xor_sync(0xffffffffu, dn, o);
            }
            dz = __shfl_sync(0xffffffffu, dz, (lane & 1) * 16);
            dn = __shfl_sync(0xffffffffu, dn, (lane & 1) * 16);
        }
        if (!builder) BAR_SYNC(12, 256);
        if (builder) {
            const uint4* src = gPart + (size_t)cta * (kTiles * 4) + lane * 4 + (t >> 5);
            auto ld = [&](uint4& v, const uint4* ptr, uint32_t on) {
                asm volatile("{\n.reg .pred p;\nsetp.ne.u32 p, %5, 0;\n"
                             "@p ld.relaxed.gpu.global.v4.u32 {%0,%1,%2,%3}, [%4];\n}\n"
                             : "+r"(v.x), "+r"(v.y), "+r"(v.z), "+r"(v.w) : "l"(ptr), "r"(on) : "memory");
            };
            auto stale = [&](const uint4& v) { return ((v.x ^ tag) | (v.y ^ tag) | (v.z ^ tag) | (v.w ^ tag)) & 3u; };
            uint4 a0 = make_uint4(~tag, 0, 0, 0), a1 = a0, a2 = a0;
            if (lane >= kTiles - 64) a2 = make_uint4(tag, tag, tag, tag);
            uint32_t p0 = 1, p1 = 1, p2 = stale(a2);
            for (int spin = 0; spin < (1 << 18); ++spin) {
                ld(a0, src, p0); ld(a1, src + 128, p1); ld(a2, src + 256, p2);
                p0 = stale(a0); p1 = stale(a1); p2 = stale(a2);
                if (spin == 0) BAR_SYNC(12, 256);
                if (!__any_sync(0xffffffffu, (p0 | p1 | p2) != 0)) break;
            }
            float s0 = __uint_as_float(a0.x & ~3u) + __uint_as_float(a1.x & ~3u) + __uint_as_float(a2.x & ~3u);
            float s1 = __uint_as_float(a0.y & ~3u) + __uint_as_float(a1.y & ~3u) + __uint_as_float(a2.y & ~3u);
            float s2 = __uint_as_float(a0.z & ~3u) + __uint_as_float(a1.z & ~3u) + __uint_as_float(a2.z & ~3u);
            float s3 = __uint_as_float(a0.w & ~3u) + __uint_as_float(a1.w & ~3u) + __uint_as_float(a2.w & ~3u);
            const bool odd = lane & 1;
            float z = (odd ? s2 : s0) + __shfl_xor_sync(0xffffffffu, odd ? s0 : s2, 1);
            float n = (odd ? s3 : s1) + __shfl_xor_sync(0xffffffffu, odd ? s1 : s3, 1);
            const bool hi = lane & 2;
            float v = (hi ? n : z) + __shfl_xor_sync(0xffffffffu, hi ? z : n, 2);
#pragma unroll
            for (int o = 4; o < 32; o <<= 1) v += __shfl_xor_sync(0xffffffffu, v, o);
            n = __shfl_down_sync(0xffffffffu, v, 2) + dn;
            z = v + dz;
            if (lane < 2) {
                out[cta * 8 + (t >> 5) * 2 + lane] = __float2bfloat16(__fdividef(n, z));
                if (!(z > 0.f && z < 3.0e38f && fabsf(n) < 3.0e38f)) sts32(sMisc + 8, 1);
            }
        }
        __syncwarp();
        BAR_ARRIVE(5, 512);
    } else {
        asm volatile("setmaxnreg.inc.sync.aligned.u32 152;");
        const int tid = T - 128;
        const int warp = tid >> 5;
        const int r = lane >> 2, q = lane & 3;
        const int wg = warp >> 2, wq = warp & 3;
        const int u = tI * 192 + warp * 16 + r;
        int4 iv = make_int4(0, 0, 0, 0);
        if (tid < 200) iv = __ldg(reinterpret_cast<const int4*>(idx + (builder ? cta : 0) * 8 * kF) + tid);
        {
            const int ur = tI * 192 + warp * 16 + (lane >> 1);
            const uint32_t dst = sbase + ST_TU + (warp * 16 + (lane >> 1)) * 80 + (lane & 1) * 32;
            const __nv_bfloat16* src = table + min(ur, kV - 1) * kD + (lane & 1) * 16;
            cp16(dst, src, ur < kV);
            cp16(dst + 16, src + 8, ur < kV);
        }
        sts128(sbase + OFF_CB + tid * 16, make_uint4(0, 0, 0, 0));
        if (tid < 120) sts128(sbase + OFF_CB + (384 + tid) * 16, make_uint4(0, 0, 0, 0));
        if (tid == 383) sts32(sMisc + 8, 0);
        asm volatile("barrier.cluster.arrive.relaxed.aligned;" ::: "memory");
        BAR_SYNC(4, 384);
        if (tid < 200) {
            const unsigned vals[4] = {(unsigned)iv.x, (unsigned)iv.y, (unsigned)iv.z, (unsigned)iv.w};
            const int row = tid / 25;
            const uint32_t rb = sbase + OFF_CB + (row >> 1) * 32 + (row & 1) * 4;
            bool badidx = false;
#pragma unroll
            for (int i = 0; i < 4; ++i) {
                badidx |= vals[i] >= (unsigned)kV;
                const unsigned v = min(vals[i], 1007u);
                const uint32_t off = rb + (v >> 4) * 128 + ((v << 2) & 24);
                const uint32_t inc = 1u << (((v << 1) & 16) + ((v & 1) << 3));
                asm volatile("red.shared.add.u32 [%0], %1;" ::"r"(off), "r"(inc) : "memory");
            }
            if (badidx) sts32(sMisc + 8, 1);
        }
        BAR_SYNC(4, 384);
        if (builder) {
            uint4* dst = gC + ((cta >> 5) * kV16 + (tid >> 3)) * 256 + (cta & 31) * 8 + (tid & 7);
            dst[0] = lds128(sbase + OFF_CB + tid * 16);
            if (tid < 120) dst[48 * 256] = lds128(sbase + OFF_CB + (384 + tid) * 16);
        }
        BAR_ARRIVE(1, 416);

        {
            uint32_t ab[8], af[8];
            asm volatile("cp.async.wait_all;" ::: "memory");
            __syncwarp();
            {
                const uint32_t la = sbase + ST_TU + (warp * 16 + (lane & 15)) * 80 + (lane >> 4) * 16;
                asm volatile("ldmatrix.sync.aligned.m8n8.x4.shared.b16 {%0,%1,%2,%3}, [%4];"
                             : "=r"(ab[0]), "=r"(ab[1]), "=r"(ab[2]), "=r"(ab[3]) : "r"(la) : "memory");
                asm volatile("ldmatrix.sync.aligned.m8n8.x4.shared.b16 {%0,%1,%2,%3}, [%4];"
                             : "=r"(ab[4]), "=r"(ab[5]), "=r"(ab[6]), "=r"(ab[7]) : "r"(la + 32) : "memory");
            }
#pragma unroll
            for (int i = 0; i < 8; ++i) af[i] = bf2h(ab[i]);
            bool bad = bf_exceeds<4>(ab[0], ab[1], ab[2], ab[3]) || bf_exceeds<4>(ab[4], ab[5], ab[6], ab[7]);

            float e[12], sv[12];
            uint32_t e2[6];
            uint32_t acc0[24], acc1[24];
            const uint64_t dG = make_desc(sbase + OFF_G, 128, 512);
            const uint32_t cst = sbase + OFF_CST;
            auto issue = [&](uint32_t (&acc)[24], int c) {
                wg_fence();
                mma_h96(acc, af[0], af[1], af[2], af[3], dG + ((c * 6144) >> 4), 0);
                mma_h96(acc, af[4], af[5], af[6], af[7], dG + ((c * 6144 + 256) >> 4), 1);
                wg_commit();
            };
            auto consume = [&](uint32_t (&acc)[24], const uint4& cb, const uint4& ch, bool first) {
                const uint32_t bb[4] = {cb.x, cb.y, cb.z, cb.w}, hh[4] = {ch.x, ch.y, ch.z, ch.w};
#pragma unroll
                for (int ai = 0; ai < 4; ++ai) {
#pragma unroll
                    for (int j = 0; j < 6; ++j)
                        e2[j] = hfma2(hadd2_relu(acc[ai * 6 + j], bb[ai]), hh[ai], (first && ai == 0) ? 0u : e2[j]);
                }
            };
            BAR_SYNC(2, 480);
            {
                const int kb = warp & 3, v8 = lane & 7;
                const uint4 tv = lds128(sbase + ST_TV + (v8 + 8 * wg) * 80 + kb * 16);
                const uint32_t wp = sbase + ST_W + (lane >> 3) * 80 + kb * 16;
                const uint32_t gaddr = sbase + OFF_G + (lane >> 3) * 1536 + wg * 512 + kb * 128 + v8 * 16;
                uint4 wr[8];
#pragma unroll
                for (int i = 0; i < 8; ++i) wr[i] = lds128(wp + i * 320);
#pragma unroll
                for (int i = 0; i < 8; ++i)
                    sts128(gaddr + i * 6144, make_uint4(hmul2(tv.x, wr[i].x), hmul2(tv.y, wr[i].y),
                                                        hmul2(tv.z, wr[i].z), hmul2(tv.w, wr[i].w)));
                asm volatile("fence.proxy.async.shared::cta;" ::: "memory");
                BAR_ARRIVE(13, 512);
                BAR_SYNC(14, 512);
            }
            wg_fence();
            mma_n24(sv, ab[0], ab[1], ab[2], ab[3], dG + (49152 >> 4), 0);
            mma_n24(sv, ab[4], ab[5], ab[6], ab[7], dG + ((49152 + 256) >> 4), 1);
            issue(acc0, 0);
            issue(acc1, 1);
            {
                const float mneg = __uint_as_float(lds32(sMisc + 12));
#pragma unroll
                for (int i = 0; i < 12; ++i) e[i] = mneg;
            }
#pragma unroll
            for (int c = 0; c < 8; c += 2) {
                {
                    const uint4 cb = lds128(cst + c * 32), ch = lds128(cst + c * 32 + 16);
                    wg_wait<1>();
                    consume(acc0, cb, ch, (c & 3) == 0);
                    if (c < 6) issue(acc0, c + 2);
                }
                {
                    const uint4 cb = lds128(cst + c * 32 + 32), ch = lds128(cst + c * 32 + 48);
                    if (c < 6) wg_wait<1>(); else wg_wait<0>();
                    consume(acc1, cb, ch, false);
                    if (c < 6) issue(acc1, c + 3);
                }
                if (c & 2) {
#pragma unroll
                    for (int j = 0; j < 6; ++j) { e[2 * j] += h_lo(e2[j]); e[2 * j + 1] += h_hi(e2[j]); }
                }
            }
            const uint32_t tagbits = (lds32(sMisc) + 1) & 3;
            const uint4 fl = lds128(sMisc + 16);
            const bool poison = bad || (fl.y | fl.z | fl.w) != 0;
            asm volatile("barrier.cluster.wait.acquire.aligned;" ::: "memory");
            float X[12], Y[12];
            float mx = 0.f, ms = 0.f;
#pragma unroll
            for (int i = 0; i < 12; ++i) {
                mx = maxnan_abs(mx, e[i]);
                ms = maxnan_abs(ms, sv[i]);
                X[i] = ex2(e[i]);
                Y[i] = X[i] * sv[i];
            }
            if (tI == (tj >> 2)) {
                const int dv = u - vb0 - 2 * q;
#pragma unroll
                for (int i = 0; i < 12; ++i) {
                    const int th = 8 * (i >> 2) + (i & 1) - 8 * ((i >> 1) & 1);
                    if (dv == th) {
                        const uint32_t dx = (__float_as_uint(X[i]) & ~3u) | tagbits, dy = (__float_as_uint(Y[i]) & ~3u) | tagbits;
                        asm volatile("st.relaxed.gpu.global.v2.u32 [%0], {%1,%2};"
                                     ::"l"(gDiag + u + 8 * ((i >> 1) & 1)), "r"(dx), "r"(dy) : "memory");
                    }
                    X[i] = (dv < th) ? X[i] : 0.f;
                    Y[i] = (dv < th) ? Y[i] : 0.f;
                }
            }
            uint32_t xh[6], yh[6];
#pragma unroll
            for (int j = 0; j < 6; ++j) {
                xh[j] = pack_bf16(X[2 * j], X[2 * j + 1]);
                yh[j] = pack_bf16(Y[2 * j], Y[2 * j + 1]);
            }
            if (!(mx <= 56.f) || !(ms <= 1.0e15f) || (ms != 0.f && ms < 1.0e-15f) || poison) xh[0] = 0x7FC07FC0u;
            const uint32_t b2 = sbase + OFF_B2 + warp * 3072 + rank * 1536;
            const uint32_t dst = b2 + lane * 16;
            asm volatile("stmatrix.sync.aligned.m8n8.x4.trans.shared.b16 [%0], {%1,%2,%3,%4};"
                         ::"r"(dst), "r"(xh[0]), "r"(xh[1]), "r"(xh[2]), "r"(xh[3]) : "memory");
            asm volatile("stmatrix.sync.aligned.m8n8.x4.trans.shared.b16 [%0], {%1,%2,%3,%4};"
                         ::"r"(dst + 512), "r"(xh[4]), "r"(xh[5]), "r"(yh[0]), "r"(yh[1]) : "memory");
            asm volatile("stmatrix.sync.aligned.m8n8.x4.trans.shared.b16 [%0], {%1,%2,%3,%4};"
                         ::"r"(dst + 1024), "r"(yh[2]), "r"(yh[3]), "r"(yh[4]), "r"(yh[5]) : "memory");
            __syncwarp();
            {
                uint32_t rdst, rbar;
                asm volatile("mapa.shared::cluster.u32 %0, %1, %2;" : "=r"(rdst) : "r"(dst), "r"(rank ^ 1));
                asm volatile("mapa.shared::cluster.u32 %0, %1, %2;" : "=r"(rbar) : "r"(sbase + OFF_BAR + 16), "r"(rank ^ 1));
#pragma unroll
                for (int i = 0; i < 3; ++i) {
                    const uint4 v = lds128(dst + i * 512);
                    asm volatile("st.async.weak.shared::cluster.mbarrier::complete_tx::bytes.v4.b32 [%0], {%1,%2,%3,%4}, [%5];"
                                 ::"r"(rdst + i * 512), "r"(v.x), "r"(v.y), "r"(v.z), "r"(v.w), "r"(rbar) : "memory");
                }
            }
        }

        {
            const uint64_t dB = make_desc(sbase + OFF_B2, 128, 256);
            const uint32_t cb0 = sbase + OFF_C + (tid & 127) * 8;
            uint32_t cb = cb0 + wg * 1024;
            uint32_t* pdst = reinterpret_cast<uint32_t*>(gPart) +
                             (((rank * 8 + wg) * 8 + wq * 2 + (r >> 2)) * kTiles + tile) * 16 + (lane & 15);
            uint32_t aA[24], aB[24];
            float acc[48];
            float z0 = 0.f, n0 = 0.f, z1 = 0.f, n1 = 0.f;
            const uint32_t tagbits = (lds32(sMisc) + 1) & 3;

            auto loadA = [&](uint32_t (&a)[24], uint32_t addr) {
#pragma unroll
                for (int s = 0; s < 6; ++s) {
                    const uint2 raw = lds64(addr + s * 4096);
                    a[4 * s + 0] = cnt2bf<0x4140>(raw.x);
                    a[4 * s + 1] = cnt2bf<0x4140>(raw.y);
                    a[4 * s + 2] = cnt2bf<0x4342>(raw.x);
                    a[4 * s + 3] = cnt2bf<0x4342>(raw.y);
                }
            };
            auto mmas = [&](uint32_t (&a)[24], int h) {
                wg_fence();
#pragma unroll
                for (int s = 0; s < 6; ++s)
                    mma_n96(acc, a[4 * s], a[4 * s + 1], a[4 * s + 2], a[4 * s + 3], dB + (((h * 6 + s) * 3072) >> 4),
                            !(h == 0 && s == 0));
                wg_commit();
            };
            auto flush = [&](uint32_t* p) {
                const bool odd = q & 1;
                float s0 = odd ? z0 : n0, k0 = odd ? n0 : z0;
                float s1 = odd ? z1 : n1, k1 = odd ? n1 : z1;
                k0 += __shfl_xor_sync(0xffffffffu, s0, 1);
                k1 += __shfl_xor_sync(0xffffffffu, s1, 1);
                const bool hi = q & 2;
                float s2 = hi ? k0 : k1, k2 = hi ? k1 : k0;
                k2 += __shfl_xor_sync(0xffffffffu, s2, 2);
                const uint32_t val = (__float_as_uint(k2) & ~3u) | tagbits;
                asm volatile("st.relaxed.gpu.global.u32 [%0], %1;" ::"l"(p), "r"(val) : "memory");
            };

            BAR_ARRIVE(15, 512);
            mbar_wait(sbase + OFF_BAR, 0);
            loadA(aA, cb);
            loadA(aB, cb + 24576);
            asm volatile("fence.proxy.async.shared::cta;" ::: "memory");
            BAR_SYNC(4, 384);
            mbar_wait_cluster(sbase + OFF_BAR + 16, 0);
            asm volatile("fence.proxy.async.shared::cta;" ::: "memory");
            const int nblk = wg < 2 ? 3 : 2;
#pragma unroll 1
            for (int it = 0; it < nblk; ++it) {
                mmas(aA, 0);
                if (it > 0) {
                    flush(pdst - 3 * 8 * kTiles * 16);
                    loadA(aB, cb + 24576);
                }
                mmas(aB, 1);
                float c0[12], c1[12];
#pragma unroll
                for (int t = 0; t < 3; ++t) {
                    const uint2 raw = lds64(cb + 49152 + t * 4096);
                    c0[4 * t + 0] = cnt2f<0x7440>(raw.x); c0[4 * t + 1] = cnt2f<0x7441>(raw.x);
                    c0[4 * t + 2] = cnt2f<0x7442>(raw.x); c0[4 * t + 3] = cnt2f<0x7443>(raw.x);
                    c1[4 * t + 0] = cnt2f<0x7440>(raw.y); c1[4 * t + 1] = cnt2f<0x7441>(raw.y);
                    c1[4 * t + 2] = cnt2f<0x7442>(raw.y); c1[4 * t + 3] = cnt2f<0x7443>(raw.y);
                }
                wg_wait<1>();
                const int nxt = wg + 3 * it + 3;
                const uint32_t cbn = cb0 + (nxt >> 2) * kQuart + (nxt & 3) * 1024;
                if (it + 1 < nblk) {
                    mbar_wait(sbase + OFF_BAR + (nxt >> 2) * 8, 0);
                    loadA(aA, cbn);
                }
                wg_wait<0>();
                float za = 0.f, zb = 0.f, zc = 0.f, zd = 0.f, na = 0.f, nb = 0.f, nc = 0.f, nd = 0.f;
#pragma unroll
                for (int vb = 0; vb < 6; ++vb) {
                    const int xb = ((vb / 3) * 6 + vb % 3) * 4, yb = xb + 12;
                    za = fmaf(acc[xb + 0], c0[2 * vb], za);
                    zb = fmaf(acc[xb + 1], c0[2 * vb + 1], zb);
                    zc = fmaf(acc[xb + 2], c1[2 * vb], zc);
                    zd = fmaf(acc[xb + 3], c1[2 * vb + 1], zd);
                    na = fmaf(acc[yb + 0], c0[2 * vb], na);
                    nb = fmaf(acc[yb + 1], c0[2 * vb + 1], nb);
                    nc = fmaf(acc[yb + 2], c1[2 * vb], nc);
                    nd = fmaf(acc[yb + 3], c1[2 * vb + 1], nd);
                }
                z0 = za + zb; z1 = zc + zd; n0 = na + nb; n1 = nc + nd;
                cb = cbn;
                pdst += 3 * 8 * kTiles * 16;
            }
            flush(pdst - 3 * 8 * kTiles * 16);
            if (wg == 2) BAR_ARRIVE(12, 256);
        }
        BAR_SYNC(5, 512);
        if (builder && lds32(sMisc + 8) != 0) fallback_rows(idx, table, ii, jj, W, bv, hv, pv, out, smem, cta * 8, tid);
    }
}

}

extern "C" void kernel_launch(void* const* d_in, const int* in_sizes, int n_in, void* d_out, int out_size) {
    (void)in_sizes; (void)n_in; (void)out_size;
    static bool init_done = false;
    static bool fits = false;
    static void *pC = nullptr, *pPart = nullptr, *pCnt = nullptr, *pDiag = nullptr;
    if (!init_done) {
        cudaFuncSetAttribute(afm_kernel, cudaFuncAttributeMaxDynamicSharedMemorySize, SMEM_BYTES);
        cudaGetSymbolAddress(&pC, g_C);
        cudaGetSymbolAddress(&pPart, g_part);
        cudaGetSymbolAddress(&pCnt, g_cnt);
        cudaGetSymbolAddress(&pDiag, g_diag);
        cudaLaunchConfig_t cfg = {};
        cfg.gridDim = dim3(kGrid);
        cfg.blockDim = dim3(kThreads);
        cfg.dynamicSmemBytes = SMEM_BYTES;
        cudaLaunchAttribute at;
        at.id = cudaLaunchAttributeClusterDimension;
        at.val.clusterDim.x = 2; at.val.clusterDim.y = 1; at.val.clusterDim.z = 1;
        cfg.attrs = &at;
        cfg.numAttrs = 1;
        int ncl = 0;
        fits = cudaOccupancyMaxActiveClusters(&ncl, afm_kernel, &cfg) == cudaSuccess && ncl >= kTiles;
        (void)cudaGetLastError();
        init_done = true;
    }
    const int* idx = (const int*)d_in[0];
    const __nv_bfloat16* table = (const __nv_bfloat16*)d_in[1];
    const int* ii = (const int*)d_in[2];
    const int* jj = (const int*)d_in[3];
    const __nv_bfloat16* W = (const __nv_bfloat16*)d_in[4];
    const __nv_bfloat16* b = (const __nv_bfloat16*)d_in[5];
    const __nv_bfloat16* h = (const __nv_bfloat16*)d_in[6];
    const __nv_bfloat16* p = (const __nv_bfloat16*)d_in[7];
    if (fits) {
        afm_kernel<<<kGrid, kThreads, SMEM_BYTES>>>(idx, table, ii, jj, W, b, h, p, (__nv_bfloat16*)d_out,
                                                    (uint4*)pC, (uint4*)pPart, (uint2*)pDiag, (unsigned*)pCnt);
    } else {
        afm_direct_kernel<<<128, 384>>>(idx, table, ii, jj, W, b, h, p, (__nv_bfloat16*)d_out);
    }
}
```
